```python
import torch

def _softmax(x, axis=-1):
    return torch.softmax(x, dim=axis)
def _gelu(x):
    return torch.nn.functional.gelu(x, approximate="tanh")
def _silu(x):
    return torch.nn.functional.silu(x)
def _sigmoid(x):
    return torch.sigmoid(x)
def _layernorm(x, axis=-1, eps=1e-5):
    m = x.mean(dim=axis, keepdim=True)
    v = x.var(dim=axis, keepdim=True, unbiased=False)
    return (x - m) / torch.sqrt(v + eps)
def _scatter_add(tgt, idx, src, axis=0):
    return tgt.clone().index_add_(axis, idx, src)
def _segment_sum(src, seg, n):
    out = torch.zeros((n,) + src.shape[1:], dtype=src.dtype)
    return out.index_add_(0, seg, src)
def _pad(x, pw):
    flat = tuple(v for pair in reversed(pw) for v in pair)
    return torch.nn.functional.pad(x, flat)

kernel_name = 'parallel_sum__ssm_conv_s4__moe_arch_mod__prompt'

def setup_inputs():

    _w = (lambda a: (lambda t: t.to(torch.bfloat16) if t.is_floating_point() else t)(torch.as_tensor(a)))
    def _A_setup():
        B, L, D, N = 1, 2048, 512, 128
        A_re = -(lambda _x: torch.exp(torch.as_tensor(_x)))((lambda *s: torch.randn(*s, dtype=torch.bfloat16) * 3.2)(D, N))
        A_im = torch.pi * (lambda *s: torch.randn(*s, dtype=torch.bfloat16) * 0.1)(D, N)
        B_re = (lambda *s: torch.randn(*s, dtype=torch.bfloat16) * 0.4)(D, N)
        B_im = (lambda *s: torch.randn(*s, dtype=torch.bfloat16) * 0.4)(D, N)
        C_re = (lambda *s: torch.randn(*s, dtype=torch.bfloat16) * 0.4)(D, N)
        C_im = (lambda *s: torch.randn(*s, dtype=torch.bfloat16) * 0.4)(D, N)
        log_dt = (lambda *s: torch.randn(*s, dtype=torch.bfloat16) * 0.1)(D) * 0.5 - 4.0
        Dskip = (lambda *s: torch.randn(*s, dtype=torch.bfloat16) * 0.1)(D)
        return {
            "u": _w((lambda *s: torch.randn(*s, dtype=torch.bfloat16) * 0.05)(B, L, D)),
            "A_re": _w(A_re),
            "A_im": _w(A_im),
            "B_re": _w(B_re),
            "B_im": _w(B_im),
            "C_re": _w(C_re),
            "C_im": _w(C_im),
            "log_dt": _w(log_dt),
            "Dskip": _w(Dskip),
        }
    _A_in = _A_setup()

    def _B_setup():
        B, S, D, F, C = 1, 2048, 512, 1792, 1
        return {
            "x": _w((lambda *s: torch.randn(*s, dtype=torch.bfloat16) * 0.05)(B, S, D)),
            "w_r": _w((lambda *s: torch.randn(*s, dtype=torch.bfloat16) * 0.05)(D)),
            "w_gate": _w((lambda *s: torch.randn(*s, dtype=torch.bfloat16) * 0.05)(D, F)),
            "w_up": _w((lambda *s: torch.randn(*s, dtype=torch.bfloat16) * 0.05)(D, F)),
            "w_down": _w((lambda *s: torch.randn(*s, dtype=torch.bfloat16) * 0.05)(F, D)),
        }
    _B_in = _B_setup()

    return {
        "A_u": _A_in["u"],
        "A_A_re": _A_in["A_re"],
        "A_A_im": _A_in["A_im"],
        "A_B_re": _A_in["B_re"],
        "A_B_im": _A_in["B_im"],
        "A_C_re": _A_in["C_re"],
        "A_C_im": _A_in["C_im"],
        "A_log_dt": _A_in["log_dt"],
        "A_Dskip": _A_in["Dskip"],
        "B_x": _B_in["x"],
        "B_w_r": _B_in["w_r"],
        "B_w_gate": _B_in["w_gate"],
        "B_w_up": _B_in["w_up"],
        "B_w_down": _B_in["w_down"],
    }

def reference(A_u, A_A_re, A_A_im, A_B_re, A_B_im, A_C_re, A_C_im, A_log_dt, A_Dskip, B_x, B_w_r, B_w_gate, B_w_up, B_w_down):
    def _A_ref(u, A_re, A_im, B_re, B_im, C_re, C_im, log_dt, Dskip):
        Bsz, L, D = u.shape
        dt = torch.exp(log_dt)[:, None]
        A = A_re + 1j * A_im
        Bc = B_re + 1j * B_im
        Cc = C_re + 1j * C_im
        logdA = dt * A
        dB = dt * Bc
        l = (lambda x, dt: x.to(dt))(torch.arange(L), A_re.dtype)
        P = torch.exp(logdA[:, :, None] * l[None, None, :])
        K = torch.einsum("dn,dnl,dn->dl", Cc, P, dB).real
        L2 = 2 * L
        Kp = _pad(K, ((0, 0), (0, L)))
        up = (lambda x, *d: x.permute(*d))(u, 0, 2, 1)
        up = _pad(up, ((0, 0), (0, 0), (0, L)))
        Kf = (lambda x, axes=(-2,-1): torch.fft.rfft2(x.float(), dim=axes))(Kp[:, None, :], axes=(-2, -1))
        Uf = (lambda x, axes=(-2,-1): torch.fft.rfft2(x.float(), dim=axes))(up[:, :, None, :], axes=(-2, -1))
        Yf = Uf * Kf[None, :, :, :]
        y = (lambda x, s, axes=(-2,-1): torch.fft.irfft2(x, s=s, dim=axes).to(torch.bfloat16))(Yf, (1, L2), axes=(-2, -1))[:, :, 0, :L]
        y = (lambda x, *d: x.permute(*d))(y, 0, 2, 1) + u * Dskip[None, None, :]
        return y

    def _B_ref(x, w_r, w_gate, w_up, w_down):
        B, S, D = x.shape
        C = 1
        r = x @ w_r
        idx = torch.argsort(-r, axis=-1)[:, :C]
        idx_e = (lambda x, n, axis: torch.repeat_interleave(x, n, dim=axis))(idx.reshape(B, C, 1), D, axis=2)
        x_sel = (lambda x, i, axis: torch.take_along_dim(x, i, dim=axis))(x, idx_e, axis=1)
        g = _silu(x_sel @ w_gate)
        u = x_sel @ w_up
        y = (g * u) @ w_down
        r_sel = _sigmoid((lambda x, i, axis: torch.take_along_dim(x, i, dim=axis))(r, idx, axis=1))
        y = y * r_sel.reshape(B, C, 1)
        b_off = (torch.arange(B) * S).reshape(B, 1)
        flat_idx = (idx + b_off).reshape(B * C)
        zero = (x * 0.0).reshape(B * S, D)
        upd = _scatter_add(zero, flat_idx, y.reshape(B * C, D), axis=0)
        return x + upd.reshape(B, S, D)

    x = A_u
    xn = _layernorm(x, axis=-1)
    return x + _A_ref(xn, A_A_re, A_A_im, A_B_re, A_B_im, A_C_re, A_C_im, A_log_dt, A_Dskip) + _B_ref(xn, B_w_r, B_w_gate, B_w_up, B_w_down)
```

```cpp
#include <cuda.h>
#include <cuda_runtime.h>
#include <cuda_bf16.h>
#include <stdint.h>

#define DEVINL __device__ __forceinline__

namespace s4moe {

constexpr int kD = 512, kF = 1792;
constexpr int kCTA = 128, kThreads = 512, kFFN = 112;
constexpr int kSpin = 1 << 18;
#define GATHER_DELAY_NS 200
#define FINAL_DELAY_NS 200

__device__ uint4 g_xnT[128 * 1024];
__device__ uint32_t g_yT[2 * 512 * 1024];
__device__ uint4 g_rec[2 * 128];
__device__ uint32_t g_hint[8 * 128];
__device__ uint32_t g_part[2 * kFFN * 512];
#define TS(i)
#define TG(i)
#define TDUMP()

constexpr int XNF_CH = (8 + 128) * 32;
constexpr int OFF_XNF = 0;
constexpr int OFF_OUT = OFF_XNF;
constexpr int PT0_W = 544, PTL_W = 48, PTH_W = 2 * 72, PTG_W = 2 * 92;
constexpr int PT_L = PT0_W, PT_H = PT_L + PTL_W, PT_G = PT_H + 4 * PTH_W, PT_CH_W = PT_G + 2 * PTG_W;
constexpr int OFF_PT = OFF_XNF + 4 * XNF_CH;
constexpr int KX_CH = 64 + 20 * 128 + 128 * 16;
constexpr int OFF_KX = OFF_PT + 4 * PT_CH_W * 4;
constexpr int OFF_YS = OFF_KX;
static_assert(4 * KX_CH >= 128 * 144, "y staging");
constexpr int MR_STR = 288, MR_EB = 128, MR_C128 = 256, MR_C2 = 264, MR_C1020 = 280, MR_WARP = 32 * MR_STR;
constexpr int KX_GEN = 64, KX_RAW = 64 + 20 * 128;
constexpr int OFF_MC = OFF_KX + 4 * KX_CH;
constexpr int WE2_P = 32, WE2_H = 113 * 16, WO2_P = 2, WO2_H = 98 * 16, W3_H = 64 * 16;
constexpr int WE2_O = 0, WO2_O = 2 * WE2_H, WO3_O = WO2_O + 2 * WO2_H, WE3_O = WO3_O + 2 * W3_H, W_CH = WE3_O + 2 * W3_H;
constexpr int OFF_W = OFF_MC;
constexpr int OFF_YT = OFF_W + 4 * W_CH;
static_assert(4 * W_CH + 16384 <= 8 * MR_WARP, "aliases of the mode tables");
constexpr int ROW = 1040;
constexpr int OFF_WG = (OFF_MC + 8 * MR_WARP + 127) / 128 * 128, OFF_WU = OFF_WG + 16384, OFF_WD = OFF_WU + 16384;
constexpr int OFF_XT = OFF_WD + 16 * ROW, OFF_XNT = OFF_XT + 16 * ROW;
constexpr int OFF_WR = OFF_XNT + 16 * ROW;
constexpr int OFF_DS = OFF_WR + 1024;
constexpr int OFF_XS = OFF_DS + 1024;
constexpr int OFF_STAT = OFF_XS + 1024;
constexpr int OFF_RP = OFF_STAT + 1024;
constexpr int OFF_FR = OFF_RP + 512;
constexpr int OFF_MS = OFF_FR + 1024;
constexpr int OFF_H = OFF_MS + 64;
constexpr int OFF_YR = OFF_H + 32;
constexpr int OFF_SEL = OFF_YR + 128;
constexpr int OFF_MBAR = OFF_SEL + 16;
constexpr int SMEM_BYTES = OFF_MBAR + 16;
static_assert(SMEM_BYTES <= 232448 - 1024, "shared memory");

enum { BAR_STAT = 1, BAR_R = 2, BAR_XN = 3, BAR_LN = 4, BAR_AUX = 5, BAR_Y = 6, BAR_YS = 12, BAR_GO = 13, BAR_FG = 14, BAR_R2 = 7, BAR_PAIR = 8   };

DEVINL void bar_sync(int id, int n) { asm volatile("bar.sync %0, %1;" ::"r"(id), "r"(n) : "memory"); }
DEVINL void bar_arrive(int id, int n) { asm volatile("bar.arrive %0, %1;" ::"r"(id), "r"(n) : "memory"); }

DEVINL uint32_t lds32(uint32_t a) { uint32_t v; asm volatile("ld.shared.u32 %0, [%1];" : "=r"(v) : "r"(a)); return v; }
DEVINL uint32_t lds16(uint32_t a) { unsigned short v; asm volatile("ld.shared.u16 %0, [%1];" : "=h"(v) : "r"(a)); return v; }
DEVINL float ldsf(uint32_t a) { float v; asm volatile("ld.shared.f32 %0, [%1];" : "=f"(v) : "r"(a)); return v; }
DEVINL uint2 lds64(uint32_t a) { uint2 v; asm volatile("ld.shared.v2.u32 {%0,%1}, [%2];" : "=r"(v.x), "=r"(v.y) : "r"(a)); return v; }
DEVINL float2 lds64f(uint32_t a) { float2 v; asm volatile("ld.shared.v2.f32 {%0,%1}, [%2];" : "=f"(v.x), "=f"(v.y) : "r"(a)); return v; }
DEVINL uint4 lds128(uint32_t a) { uint4 v; asm volatile("ld.shared.v4.u32 {%0,%1,%2,%3}, [%4];" : "=r"(v.x), "=r"(v.y), "=r"(v.z), "=r"(v.w) : "r"(a)); return v; }
DEVINL float4 lds128f(uint32_t a) { float4 v; asm volatile("ld.shared.v4.f32 {%0,%1,%2,%3}, [%4];" : "=f"(v.x), "=f"(v.y), "=f"(v.z), "=f"(v.w) : "r"(a)); return v; }
DEVINL void sts16(uint32_t a, uint32_t v) { asm volatile("st.shared.u16 [%0], %1;" ::"r"(a), "h"((unsigned short)v) : "memory"); }
DEVINL void sts32(uint32_t a, uint32_t v) { asm volatile("st.shared.u32 [%0], %1;" ::"r"(a), "r"(v) : "memory"); }
DEVINL void stsf(uint32_t a, float v) { asm volatile("st.shared.f32 [%0], %1;" ::"r"(a), "f"(v) : "memory"); }
DEVINL void sts64(uint32_t a, uint32_t x, uint32_t y) { asm volatile("st.shared.v2.u32 [%0], {%1,%2};" ::"r"(a), "r"(x), "r"(y) : "memory"); }
DEVINL void sts64f(uint32_t a, float x, float y) { asm volatile("st.shared.v2.f32 [%0], {%1,%2};" ::"r"(a), "f"(x), "f"(y) : "memory"); }
DEVINL void sts128(uint32_t a, uint4 v) { asm volatile("st.shared.v4.u32 [%0], {%1,%2,%3,%4};" ::"r"(a), "r"(v.x), "r"(v.y), "r"(v.z), "r"(v.w) : "memory"); }
DEVINL void sts128f(uint32_t a, float x, float y, float z, float w) { asm volatile("st.shared.v4.f32 [%0], {%1,%2,%3,%4};" ::"r"(a), "f"(x), "f"(y), "f"(z), "f"(w) : "memory"); }

DEVINL uint32_t ld_rlx32(const void* p) { uint32_t v; asm volatile("ld.relaxed.gpu.global.u32 %0, [%1];" : "=r"(v) : "l"(p) : "memory"); return v; }
DEVINL uint2 ld_rlx64(const void* p) { uint2 v; asm volatile("ld.relaxed.gpu.global.v2.u32 {%0,%1}, [%2];" : "=r"(v.x), "=r"(v.y) : "l"(p) : "memory"); return v; }
DEVINL uint4 ld_rlx128(const void* p) { uint4 v; asm volatile("ld.relaxed.gpu.global.v4.u32 {%0,%1,%2,%3}, [%4];" : "=r"(v.x), "=r"(v.y), "=r"(v.z), "=r"(v.w) : "l"(p) : "memory"); return v; }
DEVINL uint4 ld_acq128(const void* p) {
    uint4 v;
    asm volatile("ld.relaxed.gpu.global.v4.u32 {%0,%1,%2,%3}, [%4];" : "=r"(v.x), "=r"(v.y), "=r"(v.z), "=r"(v.w) : "l"(p) : "memory");
    return v;
}
DEVINL uint4 ld_weak128(const void* p) { uint4 v; asm volatile("ld.global.v4.u32 {%0,%1,%2,%3}, [%4];" : "=r"(v.x), "=r"(v.y), "=r"(v.z), "=r"(v.w) : "l"(p) : "memory"); return v; }
DEVINL uint32_t ld_nc32(const void* p) { uint32_t v; asm volatile("ld.global.nc.u32 %0, [%1];" : "=r"(v) : "l"(p)); return v; }
DEVINL uint32_t ld_nc16(const void* p) { unsigned short v; asm volatile("ld.global.nc.u16 %0, [%1];" : "=h"(v) : "l"(p)); return v; }
DEVINL uint32_t ld_weak32(const void* p) { uint32_t v; asm volatile("ld.global.u32 %0, [%1];" : "=r"(v) : "l"(p) : "memory"); return v; }
DEVINL void st_rlx8(void* p, uint32_t v) { asm volatile("st.relaxed.gpu.global.u8 [%0], %1;" ::"l"(p), "r"(v) : "memory"); }
DEVINL void st_rlx16(void* p, uint32_t v) { asm volatile("st.relaxed.gpu.global.u16 [%0], %1;" ::"l"(p), "h"((unsigned short)v) : "memory"); }
DEVINL void st_rlx32(void* p, uint32_t v) { asm volatile("st.relaxed.gpu.global.u32 [%0], %1;" ::"l"(p), "r"(v) : "memory"); }
DEVINL void st_rlx128(void* p, uint4 v) { asm volatile("st.relaxed.gpu.global.v4.u32 [%0], {%1,%2,%3,%4};" ::"l"(p), "r"(v.x), "r"(v.y), "r"(v.z), "r"(v.w) : "memory"); }
DEVINL void st_rlx64(void* p, uint32_t x, uint32_t y) { asm volatile("st.relaxed.gpu.global.v2.u32 [%0], {%1,%2};" ::"l"(p), "r"(x), "r"(y) : "memory"); }
DEVINL void cp_async16(uint32_t dst, const void* src) { asm volatile("cp.async.cg.shared.global [%0], [%1], 16;" ::"r"(dst), "l"(src) : "memory"); }
DEVINL void mbar_init(uint32_t a, uint32_t n) { asm volatile("mbarrier.init.shared::cta.b64 [%0], %1;" ::"r"(a), "r"(n) : "memory"); }
DEVINL void mbar_expect_tx(uint32_t a, uint32_t bytes) { asm volatile("mbarrier.arrive.expect_tx.shared::cta.b64 _, [%0], %1;" ::"r"(a), "r"(bytes) : "memory"); }
DEVINL bool mbar_try(uint32_t a, uint32_t parity) {
    uint32_t ok;
    asm volatile("{\n.reg .pred p;\nmbarrier.try_wait.parity.shared::cta.b64 p, [%1], %2;\nselp.u32 %0, 1, 0, p;\n}" : "=r"(ok) : "r"(a), "r"(parity) : "memory");
    return ok;
}
DEVINL void tma_2d(uint32_t dst, const CUtensorMap* tm, int x, int y, uint32_t mbar) {
    asm volatile("cp.async.bulk.tensor.2d.shared::cluster.global.mbarrier::complete_tx::bytes [%0], [%1, {%3, %4}], [%2];"
                 ::"r"(dst), "l"(tm), "r"(mbar), "r"(x), "r"(y) : "memory");
}
DEVINL void tma_1d(uint32_t dst, const void* src, uint32_t bytes, uint32_t mbar) {
    asm volatile("cp.async.bulk.shared::cluster.global.mbarrier::complete_tx::bytes [%0], [%1], %2, [%3];"
                 ::"r"(dst), "l"(src), "r"(bytes), "r"(mbar) : "memory");
}
DEVINL void tma_store_1d(void* dst, uint32_t src, uint32_t bytes) {
    asm volatile("cp.async.bulk.global.shared::cta.bulk_group [%0], [%1], %2;" ::"l"(dst), "r"(src), "r"(bytes) : "memory");
}

DEVINL void mma_bf16(float* d, uint32_t a0, uint32_t a1, uint32_t a2, uint32_t a3, uint32_t b0, uint32_t b1) {
    asm volatile("mma.sync.aligned.m16n8k16.row.col.f32.bf16.bf16.f32 {%0,%1,%2,%3}, {%4,%5,%6,%7}, {%8,%9}, {%0,%1,%2,%3};"
                 : "+f"(d[0]), "+f"(d[1]), "+f"(d[2]), "+f"(d[3])
                 : "r"(a0), "r"(a1), "r"(a2), "r"(a3), "r"(b0), "r"(b1));
}
DEVINL void mma_f16(float* d, uint32_t a0, uint32_t a1, uint32_t a2, uint32_t a3, uint32_t b0, uint32_t b1) {
    asm volatile("mma.sync.aligned.m16n8k16.row.col.f32.f16.f16.f32 {%0,%1,%2,%3}, {%4,%5,%6,%7}, {%8,%9}, {%0,%1,%2,%3};"
        : "+f"(d[0]), "+f"(d[1]), "+f"(d[2]), "+f"(d[3])
        : "r"(a0), "r"(a1), "r"(a2), "r"(a3), "r"(b0), "r"(b1));
}
DEVINL void ldsm_x4(uint32_t& r0, uint32_t& r1, uint32_t& r2, uint32_t& r3, uint32_t a) {
    asm volatile("ldmatrix.sync.aligned.m8n8.x4.shared.b16 {%0,%1,%2,%3}, [%4];" : "=r"(r0), "=r"(r1), "=r"(r2), "=r"(r3) : "r"(a));
}
DEVINL void ldsm_x4_t(uint32_t& r0, uint32_t& r1, uint32_t& r2, uint32_t& r3, uint32_t a) {
    asm volatile("ldmatrix.sync.aligned.m8n8.x4.trans.shared.b16 {%0,%1,%2,%3}, [%4];" : "=r"(r0), "=r"(r1), "=r"(r2), "=r"(r3) : "r"(a));
}
DEVINL void stsm_x4(uint32_t a, uint32_t r0, uint32_t r1, uint32_t r2, uint32_t r3) {
    asm volatile("stmatrix.sync.aligned.m8n8.x4.shared.b16 [%0], {%1,%2,%3,%4};" ::"r"(a), "r"(r0), "r"(r1), "r"(r2), "r"(r3) : "memory");
}
DEVINL uint32_t movm(uint32_t a) { uint32_t d; asm volatile("movmatrix.sync.aligned.m8n8.trans.b16 %0, %1;" : "=r"(d) : "r"(a)); return d; }
DEVINL uint32_t pack_bf16(float lo, float hi) { uint32_t d; asm("cvt.rn.bf16x2.f32 %0, %1, %2;" : "=r"(d) : "f"(hi), "f"(lo)); return d; }
DEVINL uint32_t pack_f16(float lo, float hi) { uint32_t d; asm("cvt.rn.f16x2.f32 %0, %1, %2;" : "=r"(d) : "f"(hi), "f"(lo)); return d; }
DEVINL float bf_lo(uint32_t w) { return __uint_as_float(w << 16); }
DEVINL float bf_hi(uint32_t w) { return __uint_as_float(w & 0xffff0000u); }
DEVINL float bf_round(float x) { return bf_lo(pack_bf16(x, 0.f)); }
DEVINL uint32_t bsub2(uint32_t a, uint32_t b) { uint32_t d; asm("sub.rn.bf16x2 %0, %1, %2;" : "=r"(d) : "r"(a), "r"(b)); return d; }
DEVINL uint32_t badd2(uint32_t a, uint32_t b) { uint32_t d; asm("add.rn.bf16x2 %0, %1, %2;" : "=r"(d) : "r"(a), "r"(b)); return d; }
DEVINL uint32_t bmul2(uint32_t a, uint32_t b) { uint32_t d; asm("mul.rn.bf16x2 %0, %1, %2;" : "=r"(d) : "r"(a), "r"(b)); return d; }
DEVINL uint32_t hmul2(uint32_t a, uint32_t b) { uint32_t d; asm("mul.rn.f16x2 %0, %1, %2;" : "=r"(d) : "r"(a), "r"(b)); return d; }
DEVINL uint32_t hfma2(uint32_t a, uint32_t b, uint32_t c) { uint32_t d; asm("fma.rn.f16x2 %0, %1, %2, %3;" : "=r"(d) : "r"(a), "r"(b), "r"(c)); return d; }
DEVINL uint32_t hneg2(uint32_t a) { uint32_t d; asm("neg.f16x2 %0, %1;" : "=r"(d) : "r"(a)); return d; }
DEVINL float ex2f(float x) { float y; asm("ex2.approx.ftz.f32 %0, %1;" : "=f"(y) : "f"(x)); return y; }
DEVINL float rcpaf(float x) { float y; asm("rcp.approx.ftz.f32 %0, %1;" : "=f"(y) : "f"(x)); return y; }
DEVINL float sqrtaf(float x) { float y; asm("sqrt.approx.ftz.f32 %0, %1;" : "=f"(y) : "f"(x)); return y; }
DEVINL float sinaf(float x) { float y; asm("sin.approx.ftz.f32 %0, %1;" : "=f"(y) : "f"(x)); return y; }
DEVINL float cosaf(float x) { float y; asm("cos.approx.ftz.f32 %0, %1;" : "=f"(y) : "f"(x)); return y; }
DEVINL uint32_t norm2(uint32_t x, uint32_t m2, float rs) { const uint32_t d = bsub2(x, m2); return pack_bf16(bf_lo(d) * rs, bf_hi(d) * rs); }

struct cf { float r, i; };
DEVINL cf cmul(cf a, cf b) { return {fmaf(a.r, b.r, -a.i * b.i), fmaf(a.r, b.i, a.i * b.r)}; }
DEVINL cf cmulc(cf a, cf b) { return {fmaf(a.r, b.r, a.i * b.i), fmaf(a.i, b.r, -a.r * b.i)}; }
DEVINL cf csq(cf a) { return {fmaf(a.r, a.r, -a.i * a.i), (a.r + a.r) * a.i}; }
DEVINL cf cexpx(float alpha, float beta, float x) {
    const float m = ex2f(alpha * x), th = beta * x;
    return {m * cosaf(th), m * sinaf(th)};
}
struct ch2 { uint32_t r, i; };
DEVINL ch2 pk(cf a, cf b) { return {pack_f16(a.r, b.r), pack_f16(a.i, b.i)}; }
DEVINL ch2 hcmul(ch2 a, ch2 b) { return {hfma2(a.r, b.r, hneg2(hmul2(a.i, b.i))), hfma2(a.r, b.i, hmul2(a.i, b.r))}; }
DEVINL ch2 hcmulc(ch2 a, ch2 b) { return {hfma2(a.r, b.r, hmul2(a.i, b.i)), hfma2(a.i, b.r, hneg2(hmul2(a.r, b.i)))}; }

struct Params {
    const __nv_bfloat16 *u, *w_r, *Dskip;
    uint4* rec;
    uint32_t* hint;
    const __nv_bfloat16 *A_re, *A_im, *B_re, *B_im, *C_re, *C_im, *log_dt;
    uint4* xnT;
    uint32_t* yT;
    uint32_t* part;
    const __nv_bfloat16 *w_gate, *w_up, *w_down;
    __nv_bfloat16* out;
    long long* dbg;
    float* dbgK;
};

__device__ __noinline__ void kgen_generic(uint32_t raw, uint32_t out, int t0, int nt, int lane) {
    const int g = lane >> 2, c = lane & 3;
#pragma unroll 1
    for (int q = 0; q < 4 * nt; q++) {
        const int t = t0 + (q >> 2), r = q & 3, j = g + 8 * (r >> 1), i = 2 * c + (r & 1);
        const int x = t == 0 ? i : t == 1 ? 128 + i : t == 2 ? ((i & 1) ? 383 + i : 256 + i)
                    : t == 3 ? (i < 4 ? 512 + 128 * i : 128 * i + 4) : 1024 + 128 * i;
        const float l = (float)(8 * j + x);
        float s = 0.f;
#pragma unroll 1
        for (int n = 0; n < 128; n++) {
            const float4 m = lds128f(raw + 16 * n);
            const float th = m.y * l;
            s += ex2f(m.x * l) * (m.z * cosaf(th) - m.w * sinaf(th));
        }
        stsf(out + q * 128 + lane * 4, s);
    }
}

struct ModeRegs { uint32_t ar, ai, br, bi, cr, ci, ldt; };
DEVINL void kgen_tables(const Params& P, const ModeRegs& q, uint32_t sb, int w, int half, int lane) {
    const uint32_t qar = q.ar, qai = q.ai, qbr = q.br, qbi = q.bi, qcr = q.cr, qci = q.ci;
    const float dt = bf_round(expf(bf_lo(q.ldt)));
    const uint32_t mr = sb + OFF_MC + (2 * w + half) * MR_WARP, kx = sb + OFF_KX + w * KX_CH + half * 16;
    TS(14);
    const float al0 = (dt * bf_lo(qar)) * 1.4426950408889634f, al1 = (dt * bf_hi(qar)) * 1.4426950408889634f;
    const float be0 = dt * bf_lo(qai), be1 = dt * bf_hi(qai);
    const cf c0 = cmul(cf{bf_lo(qcr), bf_lo(qci)}, cf{dt * bf_lo(qbr), dt * bf_lo(qbi)});
    const cf c1 = cmul(cf{bf_hi(qcr), bf_hi(qci)}, cf{dt * bf_hi(qbr), dt * bf_hi(qbi)});
    const uint32_t ex = min(__reduce_max_sync(0xffffffffu, __float_as_uint(fmaxf(fmaxf(fabsf(c0.r), fabsf(c0.i)), fmaxf(fabsf(c1.r), fabsf(c1.i))))) >> 23, 253u);
    const float scl = __uint_as_float((254u - ex) << 23), unscl = __uint_as_float(ex << 23);
    const bool grow = __any_sync(0xffffffffu, al0 > 0.f || al1 > 0.f);
    const uint32_t a = mr + lane * MR_STR;
    {
        const cf e1a = cexpx(al0, be0, 1.f), e1b = cexpx(al1, be1, 1.f), e8a = cexpx(al0, be0, 8.f), e8b = cexpx(al1, be1, 8.f);
        const cf e64a = cexpx(al0, be0, 64.f), e64b = cexpx(al1, be1, 64.f);
        const cf e2a = csq(e1a), e2b = csq(e1b), e16a = csq(e8a), e16b = csq(e8b);
        const cf e128a = csq(e64a), e128b = csq(e64b), e256a = csq(e128a), e256b = csq(e128b), e512a = csq(e256a), e512b = csq(e256b);
        const ch2 H1 = pk(e1a, e1b), H2 = pk(e2a, e2b), H4 = pk(csq(e2a), csq(e2b)), H8 = pk(e8a, e8b), H16 = pk(e16a, e16b);
        const ch2 H32 = pk(csq(e16a), csq(e16b)), H64 = pk(e64a, e64b), H128 = pk(e128a, e128b), H256 = pk(e256a, e256b), H512 = pk(e512a, e512b);
        const ch2 H383 = pk(cexpx(al0, be0, 383.f), cexpx(al1, be1, 383.f)), H1020 = pk(cexpx(al0, be0, 1020.f), cexpx(al1, be1, 1020.f));
        const cf ta = csq(csq(e512a)), tb = csq(csq(e512b));
        float k2048 = fmaf(c0.r, ta.r, -c0.i * ta.i) + fmaf(c1.r, tb.r, -c1.i * tb.i);
        ch2 L[4], M[4], Q[4];
        L[0] = ch2{0x3c003c00u, 0u}; L[1] = H1; L[2] = H2; L[3] = hcmul(H1, H2);
        M[0] = pk(cf{c0.r * scl, -c0.i * scl}, cf{c1.r * scl, -c1.i * scl});
        M[1] = hcmulc(M[0], H8); M[2] = hcmulc(M[0], H16); M[3] = hcmulc(M[1], H16);
        Q[0] = H512; Q[1] = hcmul(H512, H128); Q[2] = hcmul(H512, H256); Q[3] = hcmul(Q[1], H256);
        const uint32_t sa = 16 * ((lane >> 2) & 1);
#pragma unroll
        for (int b = 0; b < 4; b++) {
            const ch2 lu = hcmul(L[b], H4), mu = hcmulc(M[b], H32), qu = hcmul(Q[b], H4);
            const ch2 m2 = hcmulc(M[b], H64), mu2 = hcmulc(mu, H64);
            sts128(a + ((16 * b) ^ sa), make_uint4(M[b].r, m2.r, M[b].i, m2.i));
            sts128(a + 64 + ((16 * b) ^ sa), make_uint4(mu.r, mu2.r, mu.i, mu2.i));
            sts128(a + MR_EB + ((16 * b) ^ sa), make_uint4(L[b].r, L[b].i, Q[b].r, Q[b].i));
            sts128(a + MR_EB + 64 + ((16 * b) ^ sa), make_uint4(lu.r, lu.i, qu.r, qu.i));
        }
        sts128(a + MR_C128, make_uint4(H128.r, H128.i, H256.r, H256.i));
        sts128(a + MR_C128 + 16, make_uint4(H383.r, H383.i, H1020.r, H1020.i));
#pragma unroll
        for (int o = 16; o; o >>= 1) k2048 += __shfl_xor_sync(0xffffffffu, k2048, o);
        if (lane == 0) sts128f(kx, k2048, unscl, grow ? 1.f : 0.f, 0.f);
        {
            const uint32_t raw = sb + OFF_KX + w * KX_CH + KX_RAW + (64 * half + 2 * lane) * 16;
            sts128f(raw, al0, be0, c0.r, c0.i);
            sts128f(raw + 16, al1, be1, c1.r, c1.i);
        }
    }
    if (half && lane == 0 && w < 3) {
        const __nv_bfloat16* wp = w == 0 ? P.w_gate : w == 1 ? P.w_up : P.w_down;
        asm volatile("cp.async.bulk.prefetch.L2.global [%0], %1;" ::"l"(wp + (size_t)blockIdx.x * 7168), "r"(14336) : "memory");
    }
    TS(1);
    bar_sync(BAR_LN, kThreads);
}

template <int T0, int NT>
DEVINL void kgen_eval(uint32_t sb, int w, int lane, float (&kd)[NT][4]) {
    const int g = lane >> 2, c = lane & 3;
    const uint32_t mr = sb + OFF_MC + 2 * w * MR_WARP, kx = sb + OFF_KX + w * KX_CH;
    const float4 s0 = lds128f(kx), s1 = lds128f(kx + 16);
    if (s0.z == 0.f && s1.z == 0.f) {
        float tot[NT][4];
#pragma unroll 1
        for (int h = 0; h < 2; h++) {
#pragma unroll
            for (int t = 0; t < NT; t++) { kd[t][0] = kd[t][1] = kd[t][2] = kd[t][3] = 0.f; }
            const uint32_t p0 = mr + h * MR_WARP + c * MR_STR;
#pragma unroll 4
            for (int s = 0; s < 8; s++) {
                const uint32_t p = p0 + s * (4 * MR_STR);
                const uint4 A = lds128(p + 16 * (g ^ (s & 1)));
                const uint32_t pb = p + MR_EB + 16 * (g ^ (s & 1));
                if (T0 == 0) {
                    const uint2 l = lds64(pb), c1 = lds64(p + MR_C128), c2 = lds64(p + MR_C2 + 8 * (g & 1));
                    const ch2 w0 = {l.x, l.y};
                    const ch2 w1 = hcmul(w0, ch2{c1.x, c1.y}), w2 = hcmul(w0, ch2{c2.x, c2.y});
                    mma_f16(kd[0], A.x, A.y, A.z, A.w, w0.r, w0.i);
                    mma_f16(kd[1], A.x, A.y, A.z, A.w, w1.r, w1.i);
                    mma_f16(kd[NT - 1], A.x, A.y, A.z, A.w, w2.r, w2.i);
                } else {
                    const uint2 q = lds64(pb + 8), c4 = lds64(g < 4 ? p + MR_EB + 16 * (s & 1) + 8 : p + MR_C1020);
                    const ch2 w3 = {q.x, q.y};
                    const ch2 w4 = hcmul(w3, ch2{c4.x, c4.y});
                    mma_f16(kd[0], A.x, A.y, A.z, A.w, w3.r, w3.i);
                    mma_f16(kd[1], A.x, A.y, A.z, A.w, w4.r, w4.i);
                }
            }
            const float u = h ? s1.y : s0.y;
#pragma unroll
            for (int t = 0; t < NT; t++)
#pragma unroll
                for (int r = 0; r < 4; r++) { kd[t][r] = h ? fmaf(kd[t][r], u, tot[t][r]) : kd[t][r] * u; tot[t][r] = kd[t][r]; }
        }
    } else {
        const uint32_t st = kx + KX_GEN + (T0 ? 12 * 128 : 0);
        kgen_generic(kx + KX_RAW, st, T0, NT, lane);
        __syncwarp();
#pragma unroll
        for (int q = 0; q < 4 * NT; q++) kd[q >> 2][q & 3] = ldsf(st + q * 128 + lane * 4);
    }
}

DEVINL void conv_warp(const Params& P, uint32_t sb, int cta, int w, int lane) {
    const int g = lane >> 2, c = lane & 3;
    const uint32_t kx = sb + OFF_KX + w * KX_CH, pt = sb + OFF_PT + w * (PT_CH_W * 4);
    float kd[3][4];
    kgen_eval<0, 3>(sb, w, lane, kd);
    TS(2);
    float k510;
    {
        const uint32_t p0 = pt + 64 + 8 * lane;
        const int lm1 = (lane + 31) & 31, lp1 = (lane + 1) & 31;
        float rot[4], pv[4], nx[4];
        const float e[4] = {kd[2][0], kd[2][2], kd[2][1], kd[2][3]};
#pragma unroll
        for (int s = 0; s < 4; s++) {
            rot[s] = __shfl_sync(0xffffffffu, kd[s >> 1][2 * (s & 1) + 1], lm1);
            pv[s] = __shfl_sync(0xffffffffu, e[s], lm1);
            nx[s] = __shfl_sync(0xffffffffu, e[s], lp1);
        }
        const bool odd = lane & 1;
#pragma unroll
        for (int s = 0; s < 4; s++) {
            const float v0 = kd[s >> 1][2 * (s & 1)], v1 = kd[s >> 1][2 * (s & 1) + 1];
            const float prev = lane ? rot[s] : (s ? rot[s > 0 ? s - 1 : 0] : 0.f);
            sts64(p0 + 256 * s, pack_bf16(v0, prev), pack_bf16(v1, v0));
            const float nn = lane == 31 ? nx[s < 3 ? s + 1 : 3] : nx[s];
            const float lo = odd ? pv[s] : ((s == 0 && lane == 0) ? rot[3] : e[s]);
            sts64(p0 + 1024 + 256 * s, pack_bf16(e[s], lo), pack_bf16(odd ? nn : e[s], e[s]));
        }
        if (lane < 16) { sts32(pt + 4 * lane, 0u); sts32(pt + 4 * (528 + lane), 0u); }
        k510 = e[3];
        const float k508 = pv[3];
        TS(3);
        bar_sync(BAR_XN, kThreads);
        TS(4);
        if (lane == 31) {
            const float d = k510 - ldsf(kx + 32);
            sts64(p0 + 1024 + 256 * 3, pack_bf16(d, k508), pack_bf16(0.f, d));
        }
        __syncwarp();
    }
    float acc[16][4];
#pragma unroll
    for (int j = 0; j < 16; j++) { acc[j][0] = acc[j][1] = acc[j][2] = acc[j][3] = 0.f; }
    const int x0 = g - 2 * c;
    const uint32_t ptx = pt + 4 * (16 + x0);
    const uint32_t xb = sb + OFF_XNF + w * XNF_CH + (8 + g) * 32 + 8 * c;
    {
        uint32_t A[4][4];
#pragma unroll
        for (int dp = 0; dp < 4; dp++) {
            const uint32_t b = ptx + 512 * dp;
            A[dp][0] = lds32(b); A[dp][1] = lds32(b + 32); A[dp][2] = lds32(b - 32); A[dp][3] = A[dp][0];
        }
        {
            const uint32_t b = ptx + 64 * 32;
            const uint32_t a0 = lds32(b), a1 = lds32(b + 32), a2 = lds32(b - 32);
#pragma unroll
            for (int tau = 0; tau < 12; tau++) {
                const uint2 B = lds64(xb + tau * 256);
                mma_bf16(acc[tau + 4], a0, a1, a2, a0, B.x, B.y);
            }
        }
        uint32_t xr = xb, pr = ptx;
        uint2 Bn = lds64(xr), Bn2 = lds64(xr + 256);
#pragma unroll 1
        for (int rho = 0; rho < 8; rho++, xr -= 32) {
            pr += 64;
#pragma unroll
            for (int tau = 0; tau < 16; tau++) {
                const uint2 B = Bn;
                Bn = Bn2;
                Bn2 = tau < 14 ? lds64(xr + (tau + 2) * 256) : lds64(xr - 32 + (tau - 14) * 256);
#pragma unroll
                for (int dp = 3; dp >= 0; dp--)
                    if (tau + dp < 16) mma_bf16(acc[tau + dp], A[dp][0], A[dp][1], A[dp][2], A[dp][3], B.x, B.y);
                if (tau >= 12) {
                    const int dp = 15 - tau;
                    const uint32_t b = pr + 512 * dp;
                    A[dp][0] = lds32(b); A[dp][1] = lds32(b + 32); A[dp][2] = lds32(b - 32); A[dp][3] = lds32(b);
                }
            }
        }
    }
    TS(5);
    bar_sync(BAR_PAIR + w, 64);
    TS(6);
#pragma unroll
    for (int rho = 0; rho < 2; rho++) {
        const uint32_t b = ptx + 4 * PT_L + 64 * rho;
        const uint32_t a0 = lds32(b), a1 = lds32(b + 32), a2 = lds32(b - 32);
#pragma unroll
        for (int tau = 0; tau < 8; tau++) {
            const uint2 B = lds64(xb - rho * 32 + tau * 256);
            mma_bf16(acc[tau + 8], a0, a1, a2, a0, B.x, B.y);
        }
    }
    {
        const uint32_t wb = sb + OFF_W + w * W_CH;
        const int hp = (lane >> 3) & 1, row = 8 * (lane >> 4) + (lane & 7);
        uint2 tb[8];
        uint32_t aw = 0;
#pragma unroll
        for (int h = 0; h < 4; h++) {
            const int q = hp + ((h & 1) ? WE2_P : WO2_P) + (h == 2 ? -1 : h == 3 ? 1 : 0);
            aw = wb + ((h & 1) ? WE2_O + (q & 1) * WE2_H : WO2_O + (q & 1) * WO2_H) + (row + (q >> 1)) * 16;
            const uint32_t tp = pt + 4 * (PT_H + h * PTH_W) + 8 * (16 + x0);
#pragma unroll
            for (int i = 0; i < 6; i++) tb[i] = lds64(tp + 64 * i);
#pragma unroll
            for (int kap = 0; kap < 6; kap++) {
                uint32_t a0, a1, a2, a3;
                ldsm_x4_t(a0, a1, a2, a3, aw + 256 * kap);
#pragma unroll
                for (int d = 0; d < 6; d++)
                    if (4 + 2 * kap + d < 16) mma_bf16(acc[4 + 2 * kap + d], a0, a1, a2, a3, tb[d].x, tb[d].y);
            }
        }
        {
            uint32_t a0, a1, a2, a3;
            ldsm_x4_t(a0, a1, a2, a3, aw - 256);
#pragma unroll
            for (int d = 1; d < 6; d++) mma_bf16(acc[2 + d], a0, a1, a2, a3, tb[d].x, tb[d].y);
        }
#pragma unroll
        for (int gp = 0; gp < 2; gp++) {
            const uint32_t aw3 = wb + (gp ? WE3_O : WO3_O) + hp * W3_H + row * 16;
            const uint32_t tp = pt + 4 * (PT_G + gp * PTG_W) + 8 * (16 + x0);
#pragma unroll
            for (int i = 0; i < 8; i++) tb[i] = lds64(tp + 64 * i);
#pragma unroll
            for (int kap = 0; kap < 4; kap++) {
                uint32_t a0, a1, a2, a3;
                ldsm_x4_t(a0, a1, a2, a3, aw3 + 256 * kap);
#pragma unroll
                for (int d = 0; d < 8; d++)
                    if (8 + 2 * kap + d < 16) mma_bf16(acc[8 + 2 * kap + d], a0, a1, a2, a3, tb[d].x, tb[d].y);
            }
        }
    }
    TS(7);
    if (w == 0 && lane < 8) st_rlx8((uint8_t*)(P.hint + lane * 128 + cta) + 3, lds32(sb + OFF_SEL + 8));
    {
        const uint32_t ys = sb + OFF_YS + (2 * c * 36 + 8 * w + g) * 4;
#pragma unroll
        for (int j = 0; j < 16; j++) {
            sts32(ys + j * (8 * 144), ~pack_bf16(acc[j][0], acc[j][2]));
            sts32(ys + j * (8 * 144) + 144, ~pack_bf16(acc[j][1], acc[j][3]));
        }
    }
    TS(8);
}

DEVINL void y_exchange(const Params& P, uint32_t sb, int cta, int t) {
    bar_sync(BAR_YS, 256);
    const uint32_t tag = lds32(sb + OFF_SEL + 8);
    uint4* base = (uint4*)P.yT + (size_t)(tag & 1) * (128 * 1024);
#pragma unroll
    for (int r = 0; r < 4; r++) {
        const int u = t + 256 * r;
        st_rlx128(base + (size_t)(u >> 3) * 1024 + cta * 8 + (u & 7), lds128(sb + OFF_YS + (u >> 3) * 144 + (u & 7) * 16));
    }
    TS(10);
    if (t >= 224) {
#pragma unroll 1
        for (int it = 0; it < kSpin; it++) {
            const uint4 h = ld_rlx128(P.hint + (cta & 7) * 128 + 4 * (t - 224));
            const uint32_t t8 = tag << 24;
            if (__all_sync(0xffffffffu, (((h.x ^ t8) | (h.y ^ t8) | (h.z ^ t8) | (h.w ^ t8)) >> 24) == 0)) break;
        }
    }
    bar_sync(BAR_YS, 256);
    TS(12);
    const uint4* src = base + (size_t)cta * 1024 + t;
    uint4 v[4];
#pragma unroll
    for (int r = 0; r < 4; r++) v[r] = ld_weak128(src + 256 * r);
#pragma unroll 1
    for (int it = 0; it < kSpin; it++) {
        bool ok = true;
#pragma unroll
        for (int r = 0; r < 4; r++) ok = ok && v[r].x != 0u && v[r].y != 0u && v[r].z != 0u && v[r].w != 0u;
        if (__all_sync(0xffffffffu, ok)) break;
#pragma unroll
        for (int r = 0; r < 4; r++) if (v[r].x == 0u || v[r].y == 0u || v[r].z == 0u || v[r].w == 0u) v[r] = ld_rlx128(src + 256 * r);
    }
#pragma unroll
    for (int r = 0; r < 4; r++) sts128(sb + OFF_YT + (t + 256 * r) * 16, v[r]);
    bar_arrive(BAR_Y, kThreads);
    TS(11); TDUMP();
}

DEVINL void help_warp(const Params& P, uint32_t sb, int cta, int w, int lane) {
    const int g = lane >> 2, c = lane & 3;
    const uint32_t kx = sb + OFF_KX + w * KX_CH, pt = sb + OFF_PT + w * (PT_CH_W * 4);
    float kd[2][4];
    kgen_eval<3, 2>(sb, w, lane, kd);
    TS(2);
    {
        if (lane == 0) stsf(kx + 32, kd[0][0]);
        auto put = [](uint32_t a, uint32_t v) { sts16(a, v); sts16(a + 10, v); sts16(a + 68, v); sts16(a + 78, v); };
        const int h = ((c >> 1) + 2 * (g & 1) + 3) & 3, gp = (g & 1) ^ 1;
        const uint32_t a3 = pt + 4 * (PT_H + h * PTH_W) + 8 * (16 + 16 * (c & 1) + (g >> 1));
        const uint32_t a4 = pt + 4 * (PT_G + gp * PTG_W) + 8 * (16 + 16 * c + (g >> 1) - gp);
#pragma unroll
        for (int q = 0; q < 8; q++) {
            const int r = q & 3;
            const uint32_t a = ((q >> 2) ? a4 : a3) + 8 * (8 * (r & 1) + 4 * (r >> 1));
            put((q == 4 && lane == 0) ? pt + 4 * (PT_H + 3 * PTH_W) + 8 * (16 + 32) : a, pack_bf16(kd[q >> 2][r], 0.f));
        }
        if (lane == 0) {
            const uint32_t v = pack_bf16(kd[1][0], 0.f), al = pt + 4 * (PT_L + 16 + 3);
            sts16(al, v); sts16(al + 4, v); sts16(al + 6, v); sts16(al + 10, v);
            put(pt + 4 * (PT_G + PTG_W) + 8 * (16 + 63), pack_bf16(ldsf(kx) + ldsf(kx + 16), 0.f));
        }
    }
    TS(3);
    bar_sync(BAR_XN, kThreads);
    TS(4);
    const uint32_t wb = sb + OFF_W + w * W_CH;
    {
        const uint4 z = make_uint4(0, 0, 0, 0);
        sts128(wb + WE2_O + (lane & 1) * WE2_H + (lane >> 1) * 16, z);
        if (lane < 2) sts128(wb + WO2_O + lane * WO2_H, z);
    }
#pragma unroll 1
    for (int b = lane; b < 96; b += 32) {
        const uint32_t xa = sb + OFF_XNF + w * XNF_CH + (8 + b - 2) * 32;
        const uint4 p1 = lds128(xa + 16);
        const uint4 q0 = lds128(xa + 32), q1 = lds128(xa + 48);
        const uint4 r0 = lds128(xa + 64), r1 = lds128(xa + 80);
        const uint32_t u[17] = {p1.y, p1.w, q0.x, q0.z, q1.x, q1.z, q0.y, q0.w, q1.y, q1.w, r0.x, r0.z, r1.x, r1.z, r0.y, r0.w, r1.y};
        float C[34];
        C[0] = 0.f;
#pragma unroll
        for (int i = 0; i < 33; i++) C[i + 1] = C[i] + ((i & 1) ? bf_hi(u[i >> 1]) : bf_lo(u[i >> 1]));
#pragma unroll
        for (int hh = 0; hh < 2; hh++) {
            uint32_t o2[4], e2[4];
#pragma unroll
            for (int i = 0; i < 4; i++) {
                const int t = 8 * hh + 2 * i;
                o2[i] = pack_bf16(C[t + 18] - C[t + 15], C[t + 19] - C[t + 16]);
                e2[i] = pack_bf16(C[t + 15] - C[t + 10], C[t + 16] - C[t + 11]);
            }
            sts128(wb + b * 16 + WO2_O + hh * WO2_H + (WO2_P / 2) * 16, make_uint4(o2[0], o2[1], o2[2], o2[3]));
            sts128(wb + b * 16 + WE2_O + hh * WE2_H + (WE2_P / 2) * 16, make_uint4(e2[0], e2[1], e2[2], e2[3]));
        }
        if (b < 64) {
#pragma unroll
            for (int hh = 0; hh < 2; hh++) {
                uint32_t o3[4], e3[4];
#pragma unroll
                for (int i = 0; i < 4; i++) {
                    const int t = 8 * hh + 2 * i;
                    o3[i] = pack_bf16(C[t + 16] - C[t + 9], C[t + 17] - C[t + 10]);
                    e3[i] = pack_bf16(C[t + 9] - C[t + 0], C[t + 10] - C[t + 1]);
                }
                sts128(wb + b * 16 + WO3_O + hh * W3_H, make_uint4(o3[0], o3[1], o3[2], o3[3]));
                sts128(wb + b * 16 + WE3_O + hh * W3_H, make_uint4(e3[0], e3[1], e3[2], e3[3]));
            }
        }
    }
    if (lane < 8) {
        float s = 0.f;
#pragma unroll 1
        for (int j = 6; j <= 10; j++) {
            const int t = 1536 + lane - j, p = t & 15;
            s += __uint_as_float(lds16(sb + OFF_XNF + w * XNF_CH + (8 + (t >> 4)) * 32 + 8 * ((p & 7) >> 1) + 4 * (p >> 3) + 2 * (p & 1)) << 16);
        }
        sts16(wb + WE2_O + (96 + WE2_P / 2) * 16 + 2 * lane, pack_bf16(s, 0.f));
    }
    bar_arrive(BAR_PAIR + w, 64);
    TS(5);
    {
        const uint32_t tag = lds32(sb + OFF_SEL + 8);
        uint4* zy = (uint4*)P.yT + (size_t)((tag & 1) ^ 1) * (128 * 1024) + (size_t)cta * 1024 + 32 * w + lane;
#pragma unroll
        for (int r = 0; r < 8; r++) zy[128 * r] = make_uint4(0, 0, 0, 0);
    }
}

extern __shared__ __align__(128) unsigned char smem_generic[];
DEVINL void aux_warp(const Params& P, const CUtensorMap* tmG, const CUtensorMap* tmU, uint32_t sb, int cta, int hw, int lane, uint32_t prev_rec) {
    const int g = lane >> 2, c = lane & 3;
    const int tid = hw * 32 + lane;
    uint32_t* const rec = (uint32_t*)&P.rec[2 * cta];
    const uint32_t tag = (prev_rec + 1u) & 0xffffu;
    if (tid == 0) {
        mbar_init(sb + OFF_MBAR, 1);
        asm volatile("fence.mbarrier_init.release.cluster;\nfence.proxy.async.shared::cta;" ::: "memory");
    }
    asm volatile("cp.async.wait_group 0;" ::: "memory");
    TS(5);
    bar_sync(BAR_STAT, 256);
    const uint32_t ta = ((lane & 7) + 8 * ((lane >> 3) & 1)) * ROW + (64 * hw + 8 * (lane >> 4)) * 2;
    uint32_t xa[4][4];
#pragma unroll
    for (int k = 0; k < 4; k++) ldsm_x4(xa[k][0], xa[k][1], xa[k][2], xa[k][3], sb + OFF_XT + ta + 32 * k);
    {
        float aS[4] = {0, 0, 0, 0}, aG0[4] = {0, 0, 0, 0}, aG1[4] = {0, 0, 0, 0};
#pragma unroll
        for (int k = 0; k < 4; k++) {
            mma_bf16(aS, xa[k][0], xa[k][1], xa[k][2], xa[k][3], 0x3f803f80u, 0x3f803f80u);
            mma_bf16(aG0, xa[k][0], xa[k][1], xa[k][2], xa[k][3], xa[k][0], xa[k][2]);
            mma_bf16(aG1, xa[k][0], xa[k][1], xa[k][2], xa[k][3], xa[k][1], xa[k][3]);
        }
        if (c == (g >> 1)) {
            sts64f(sb + OFF_STAT + hw * 128 + g * 8, aS[0], (g & 1) ? aG0[1] : aG0[0]);
            sts64f(sb + OFF_STAT + hw * 128 + (g + 8) * 8, aS[2], (g & 1) ? aG1[3] : aG1[2]);
        }
    }
    TS(1);
    bar_sync(BAR_STAT, 256);
    uint32_t m2[2];
    float rs[2];
    {
        const int t = g + 8 * (c & 1);
        float2 pv[8];
#pragma unroll
        for (int k = 0; k < 8; k++) pv[k] = lds64f(sb + OFF_STAT + k * 128 + t * 8);
        const float s = ((pv[0].x + pv[1].x) + (pv[2].x + pv[3].x)) + ((pv[4].x + pv[5].x) + (pv[6].x + pv[7].x));
        const float q = ((pv[0].y + pv[1].y) + (pv[2].y + pv[3].y)) + ((pv[4].y + pv[5].y) + (pv[6].y + pv[7].y));
        const float mean = s * (1.f / 512.f);
        const float var = fmaxf(fmaf(-mean, mean, q * (1.f / 512.f)), 0.f);
        const uint32_t mm = pack_bf16(mean, mean);
        const float sd = bf_round(sqrtaf(bf_round(bf_round(var) + 1e-5f)));
        const float rr = rcpaf(sd);
        if (tid < 32 && c < 2) sts32(sb + OFF_MS + 4 * t, (mm << 16) | (__float_as_uint(sd) >> 16));
        const uint32_t mo = __shfl_xor_sync(0xffffffffu, mm, 1);
        const float ro = __shfl_xor_sync(0xffffffffu, rr, 1);
        m2[0] = (c & 1) ? mo : mm; m2[1] = (c & 1) ? mm : mo;
        rs[0] = (c & 1) ? ro : rr; rs[1] = (c & 1) ? rr : ro;
    }
    {
        char* dst = (char*)P.xnT + (size_t)(16 * hw + (g >> 2)) * 16384 + cta * 128 + (g & 3) * 32 + 8 * c;
        if (tid < 8) { st_rlx16(P.hint + tid * 128 + cta, tag); sts32(sb + OFF_SEL + 8, tag); }
#pragma unroll
        for (int k = 0; k < 4; k++) {
#pragma unroll
            for (int r = 0; r < 4; r++) xa[k][r] = norm2(xa[k][r], m2[r & 1], rs[r & 1]);
            st_rlx64(dst + (size_t)k * (4 * 16384), ~movm(xa[k][0]), movm(xa[k][1]));
            st_rlx64(dst + (size_t)k * (4 * 16384) + 2 * 16384, ~movm(xa[k][2]), movm(xa[k][3]));
        }
    }
    TS(14);
    bar_arrive(BAR_LN, kThreads);

    {
        float aR[4] = {0, 0, 0, 0};
#pragma unroll
        for (int k = 0; k < 4; k++) {
            const uint32_t wr = sb + OFF_WR + (32 * hw + 8 * k + c) * 4;
            mma_bf16(aR, xa[k][0], xa[k][1], xa[k][2], xa[k][3], lds32(wr), lds32(wr + 16));
            stsm_x4(sb + OFF_XNT + ta + 32 * k, xa[k][0], xa[k][1], xa[k][2], xa[k][3]);
        }
        if (c == 0) { stsf(sb + OFF_RP + g * 32 + hw * 4, aR[0]); stsf(sb + OFF_RP + (g + 8) * 32 + hw * 4, aR[2]); }
    }
    if (hw != 0) bar_arrive(BAR_R2, 256);
    else {
        bar_sync(BAR_R2, 256);
        const int t = lane & 15;
        const float4 v0 = lds128f(sb + OFF_RP + t * 32), v1 = lds128f(sb + OFF_RP + t * 32 + 16);
        const uint32_t rb = pack_bf16(((v0.x + v0.y) + (v0.z + v0.w)) + ((v1.x + v1.y) + (v1.z + v1.w)), 0.f);
        const uint32_t ord = (rb & 0x8000u) ? (~rb & 0xffffu) : (rb | 0x8000u);
        const uint32_t key = __reduce_max_sync(0xffffffffu, (ord << 16) | ((tag & 31u) << 11) | (uint32_t)(2047 - (16 * cta + t)));
        if (lane == 0) st_rlx64(rec, key, lds32(sb + OFF_MS + 4 * ((2047 - key) & 15)));
#pragma unroll 1
        for (int it = 0; it < kSpin; it++) {
            const uint4 h = ld_rlx128(P.hint + (cta & 7) * 128 + 4 * lane);
            if (__all_sync(0xffffffffu, (((h.x ^ tag) | (h.y ^ tag) | (h.z ^ tag) | (h.w ^ tag)) & 0xffffu) == 0)) break;
        }
    }
    TS(2);
    bar_sync(BAR_AUX, 256);
    TS(3);
    uint32_t key, xsel = 0, msw;
    {
        uint4* src = P.xnT + (size_t)cta * 1024 + tid;
        uint4 v[4];
#pragma unroll
        for (int r = 0; r < 4; r++) v[r] = ld_weak128(src + 256 * r);
        if (hw == 1) {
            const uint32_t tag5 = (tag & 31u) << 11;
#pragma unroll 1
            for (int it = 0; it < kSpin; it++) {
                uint32_t bad = 0;
                key = 0; msw = 0;
#pragma unroll
                for (int i = 0; i < 4; i++) {
                    const uint2 k2 = ld_rlx64(&P.rec[2 * (lane + 32 * i)]);
                    bad |= (k2.x & 0xf800u) ^ tag5;
                    if (k2.x > key) { key = k2.x; msw = k2.y; }
                }
                if (__all_sync(0xffffffffu, bad == 0)) break;
            }
            if (key == __reduce_max_sync(0xffffffffu, key)) sts64(sb + OFF_SEL, key, msw);
        }
        bar_sync(BAR_AUX, 256);
        { const uint2 km = lds64(sb + OFF_SEL); key = km.x; msw = km.y; }
        if (cta < kFFN) xsel = ld_weak32((const uint32_t*)(P.u + (size_t)(2047 - (int)(key & 2047u)) * kD) + tid);
#pragma unroll 1
        for (int it = 0; it < kSpin; it++) {
            bool ok = true;
#pragma unroll
            for (int r = 0; r < 4; r++) ok = ok && v[r].x != 0u && v[r].z != 0u;
            if (__all_sync(0xffffffffu, ok)) break;
#pragma unroll
            for (int r = 0; r < 4; r++) if (v[r].x == 0u || v[r].z == 0u) v[r] = ld_rlx128(src + 256 * r);
        }
        const uint32_t dst = sb + OFF_XNF + ((tid >> 1) & 3) * XNF_CH + 256 + (tid >> 3) * 32 + (tid & 1) * 16;
#pragma unroll
        for (int r = 0; r < 4; r++) sts128(dst + r * 1024, make_uint4(~v[r].x, v[r].y, ~v[r].z, v[r].w));
        bar_arrive(BAR_XN, kThreads);
        TS(4);
        sts32(sb + OFF_XS + 4 * tid, norm2(xsel, __byte_perm(msw, 0, 0x3232), rcpaf(__uint_as_float(msw << 16))));
        if (cta < kFFN && lane == 0) {
            const uint32_t mb = sb + OFF_MBAR;
            if (hw == 0) mbar_expect_tx(mb, 3 * 16384);
            if (hw < 4) tma_2d(sb + ((hw & 2) ? OFF_WU : OFF_WG) + (hw & 1) * 8192, (hw & 2) ? tmU : tmG, 16 * cta, (hw & 1) * 256, mb);
            tma_1d(sb + OFF_WD + (2 * hw) * ROW, P.w_down + (size_t)(16 * cta + 2 * hw) * kD, 1024, mb);
            tma_1d(sb + OFF_WD + (2 * hw + 1) * ROW, P.w_down + (size_t)(16 * cta + 2 * hw + 1) * kD, 1024, mb);
        }
        __syncwarp();
#pragma unroll
        for (int r = 0; r < 4; r++) src[256 * r] = make_uint4(0, 0, 0, 0);
    }
    const int idx = 2047 - (int)(key & 2047u);
    {
        const uint4 z = make_uint4(0, 0, 0, 0);
        if (cta < kFFN && tid < 128) ((uint4*)P.part)[((tag & 1) ^ 1) * (kFFN * 128) + cta * 128 + tid] = z;
    }
    TS(6);
    if (hw == 0 && cta < kFFN) {
#pragma unroll 1
        for (int it = 0; it < kSpin && !mbar_try(sb + OFF_MBAR, 0); it++) { }
    }
    bar_sync(BAR_AUX, 256);
    if (hw >= 4) TS(13);
    if (cta < kFFN) {
        {
            float ag[4] = {0, 0, 0, 0}, au[4] = {0, 0, 0, 0};
            const uint32_t wa = sb + OFF_WG + (64 * hw + 8 * (lane >> 4) + (lane & 7)) * 32 + 16 * ((lane >> 3) & 1);
#pragma unroll 2
            for (int k = 0; k < 4; k++) {
                const uint32_t xs = sb + OFF_XS + (32 * hw + 8 * k + c) * 4;
                const uint32_t b0 = lds32(xs), b1 = lds32(xs + 16);
                uint32_t a0, a1, a2, a3;
                ldsm_x4_t(a0, a1, a2, a3, wa + 512 * k);
                mma_bf16(ag, a0, a1, a2, a3, b0, b1);
                ldsm_x4_t(a0, a1, a2, a3, wa + 16384 + 512 * k);
                mma_bf16(au, a0, a1, a2, a3, b0, b1);
            }
            if (c == 0) {
                const uint32_t fr = sb + OFF_FR + hw * 128 + 4 * g;
                stsf(fr, ag[0]); stsf(fr + 32, ag[2]); stsf(fr + 64, au[0]); stsf(fr + 96, au[2]);
            }
        }
        bar_sync(BAR_AUX, 256);
        {
            float gs = 0.f, us = 0.f;
#pragma unroll
            for (int k = 0; k < 4; k++) {
                const uint32_t fr = sb + OFF_FR + (4 * (lane >> 4) + k) * 128 + 4 * (lane & 15);
                gs += ldsf(fr); us += ldsf(fr + 64);
            }
            gs += __shfl_xor_sync(0xffffffffu, gs, 16); us += __shfl_xor_sync(0xffffffffu, us, 16);
            const float gb = bf_round(gs);
            const float hv = bf_round(bf_round(__fdividef(gb, 1.f + __expf(-gb))) * bf_round(us));
            const uint32_t b0 = pack_bf16(__shfl_sync(0xffffffffu, hv, 2 * c), __shfl_sync(0xffffffffu, hv, 2 * c + 1));
            const uint32_t b1 = pack_bf16(__shfl_sync(0xffffffffu, hv, 2 * c + 8), __shfl_sync(0xffffffffu, hv, 2 * c + 9));
            const uint32_t wa = sb + OFF_WD + (8 * (lane >> 4) + (lane & 7)) * ROW + (64 * hw + 8 * ((lane >> 3) & 1)) * 2;
            float y0 = 0.f, y1 = 0.f;
#pragma unroll
            for (int m = 0; m < 4; m++) {
                float d[4] = {0, 0, 0, 0};
                uint32_t a0, a1, a2, a3;
                ldsm_x4_t(a0, a1, a2, a3, wa + 32 * m);
                mma_bf16(d, a0, a1, a2, a3, b0, b1);
                if (c == m) { y0 = d[0]; y1 = d[2]; }
            }
            uint32_t* dst = P.part + (size_t)(tag & 1) * (kFFN * 512) + cta * 512 + 64 * hw + 16 * c + g;
            st_rlx32(dst, ~__float_as_uint(y0));
            st_rlx32(dst + 8, ~__float_as_uint(y1));
        }
        bar_sync(BAR_AUX, 256);
        if (tid < 8) st_rlx8((uint8_t*)(P.hint + tid * 128 + cta) + 2, tag);
    }
    TS(8);
    if (hw == 0) {
#pragma unroll 1
        for (int it = 0; it < kSpin; it++) {
            const uint4 h = ld_rlx128(P.hint + (cta & 7) * 128 + 4 * min(lane, kFFN / 4 - 1));
            const uint32_t t8 = tag << 16;
            if (__all_sync(0xffffffffu, (((h.x ^ t8) | (h.y ^ t8) | (h.z ^ t8) | (h.w ^ t8)) & 0xff0000u) == 0)) break;
        }
    }
    bar_sync(BAR_AUX, 256);
    {
        if (hw < 4) {
            const uint32_t* src = P.part + (size_t)(tag & 1) * (kFFN * 512) + min(tid, kFFN - 1) * 512 + 4 * cta;
            uint4 p;
#pragma unroll 1
            for (int it = 0; it < kSpin; it++) {
                p = ld_rlx128(src);
                if (__all_sync(0xffffffffu, p.x != 0u && p.y != 0u && p.z != 0u && p.w != 0u)) break;
            }
            const bool on = tid < kFFN;
            float y0 = on ? __uint_as_float(~p.x) : 0.f, y1 = on ? __uint_as_float(~p.y) : 0.f;
            float y2 = on ? __uint_as_float(~p.z) : 0.f, y3 = on ? __uint_as_float(~p.w) : 0.f;
            TS(13);
#pragma unroll
            for (int o = 1; o <= 16; o <<= 1) {
                y0 += __shfl_xor_sync(0xffffffffu, y0, o); y1 += __shfl_xor_sync(0xffffffffu, y1, o);
                y2 += __shfl_xor_sync(0xffffffffu, y2, o); y3 += __shfl_xor_sync(0xffffffffu, y3, o);
            }
            if (lane == 0) sts128f(sb + OFF_YR + hw * 16, y0, y1, y2, y3);
        }
        TS(7);
        bar_sync(BAR_AUX, 256);
        if (tid < 4) {
            float y = 0.f;
#pragma unroll
            for (int k = 0; k < 4; k++) y += ldsf(sb + OFF_YR + k * 16 + 4 * tid);
            const uint32_t ord = key >> 16;
            const float r = __uint_as_float(((ord & 0x8000u) ? (ord & 0x7fffu) : (~ord & 0xffffu)) << 16);
            const float rsel = bf_round(__fdividef(1.f, 1.f + __expf(-r)));
            st_rlx32(rec + 4 + tid, (tag << 16) | (pack_bf16(bf_round(y) * rsel, 0.f) & 0xffffu));
        }
    }
    TS(9);
    {
        const int tsel = ((idx >> 4) == cta) ? (idx & 15) : -1;
        TS(10);
        bar_sync(BAR_Y, kThreads);
        TS(11);
#pragma unroll 2
        for (int k = 0; k < 4; k++) {
            uint32_t x[4], n[4];
            ldsm_x4(x[0], x[1], x[2], x[3], sb + OFF_XT + ta + 32 * k);
            ldsm_x4(n[0], n[1], n[2], n[3], sb + OFF_XNT + ta + 32 * k);
#pragma unroll
            for (int hc = 0; hc < 2; hc++) {
                const int cp = 32 * hw + 8 * k + 4 * hc + c;
                const uint32_t y0 = ~lds32(sb + OFF_YT + cp * 64 + g * 4), y1 = ~lds32(sb + OFF_YT + cp * 64 + 32 + g * 4);
                const uint32_t ds = lds32(sb + OFF_DS + 4 * cp);
#pragma unroll
                for (int ht = 0; ht < 2; ht++) {
                    const int r = ht + 2 * hc;
                    const uint32_t yb = __byte_perm(y0, y1, ht ? 0x7632 : 0x5410);
                    x[r] = badd2(badd2(x[r], badd2(yb, bmul2(n[r], ds))), n[r]);
                }
            }
            stsm_x4(sb + OFF_OUT + ta + 32 * k, x[0], x[1], x[2], x[3]);
        }
        asm volatile("fence.proxy.async.shared::cta;" ::: "memory");
        bar_sync(BAR_AUX, 256);
        if (tid < 16 && tid != tsel) {
            tma_store_1d(P.out + (size_t)(16 * cta + tid) * kD, sb + OFF_OUT + tid * ROW, 1024);
            asm volatile("cp.async.bulk.commit_group;\ncp.async.bulk.wait_group.read 0;" ::: "memory");
        }
        if (tsel >= 0) {
            const uint32_t* us = (const uint32_t*)&P.rec[2 * (tid >> 1) + 1] + 2 * (tid & 1);
            const uint32_t xw = lds32(sb + OFF_XT + tsel * ROW + 4 * tid), nw = lds32(sb + OFF_XNT + tsel * ROW + 4 * tid);
            const uint32_t yo = sb + OFF_YT + tid * 64 + (tsel & 7) * 4;
            const uint32_t yb = __byte_perm(~lds32(yo), ~lds32(yo + 32), (tsel & 8) ? 0x7632 : 0x5410);
            const uint32_t s1 = badd2(xw, badd2(yb, bmul2(nw, lds32(sb + OFF_DS + 4 * tid))));
            uint32_t a, b;
#pragma unroll 1
            for (int it = 0; it < kSpin; it++) {
                a = ld_rlx32(us); b = ld_rlx32(us + 1);
                if (__all_sync(0xffffffffu, (a >> 16) == tag && (b >> 16) == tag)) break;
            }
            ((uint32_t*)(P.out + (size_t)idx * kD))[tid] = badd2(s1, badd2(nw, __byte_perm(a, b, 0x5410)));
        }
    }
    TS(12); TDUMP();
}

__global__ void __launch_bounds__(kThreads, 1) fused_kernel(const Params P, const __grid_constant__ CUtensorMap tmG,
                                                             const __grid_constant__ CUtensorMap tmU) {
    extern __shared__ __align__(128) unsigned char smem[];
    const uint32_t sb = (uint32_t)__cvta_generic_to_shared(smem);
    const int warp = threadIdx.x >> 5, lane = threadIdx.x & 31;
    const int cta = blockIdx.x;
    const int w = warp & 3, half = (warp >> 2) & 1;
    TS(0);
    ModeRegs q;
    uint32_t prev_rec = 0;
    if (warp >= 8) {
        {
        const size_t po = (size_t)(4 * cta + w) * 128 + 64 * half + 2 * lane;
        q.ar = ld_nc32(P.A_re + po); q.ai = ld_nc32(P.A_im + po); q.br = ld_nc32(P.B_re + po);
        q.bi = ld_nc32(P.B_im + po); q.cr = ld_nc32(P.C_re + po); q.ci = ld_nc32(P.C_im + po);
        q.ldt = ld_nc16(P.log_dt + 4 * cta + w);
        }
        bar_arrive(BAR_GO, kThreads);
    } else {
        const int tid = threadIdx.x;
        bar_sync(BAR_GO, kThreads);
        const uint32_t xd = sb + OFF_XT + (tid >> 6) * ROW + (tid & 63) * 16;
        const __nv_bfloat16* xs = P.u + (size_t)cta * 16 * kD + tid * 8;
#pragma unroll
        for (int i = 0; i < 4; i++) cp_async16(xd + 4 * ROW * i, xs + 2048 * i);
        if (tid < 128) cp_async16(sb + OFF_WR + tid * 16, (tid < 64 ? P.w_r : P.Dskip - 512) + tid * 8);
        asm volatile("cp.async.commit_group;" ::: "memory");
        prev_rec = ld_rlx32(P.hint + (cta & 7) * 128 + cta);
        aux_warp(P, &tmG, &tmU, sb, cta, warp, lane, prev_rec);
        return;
    }
    if (half) {
        const uint32_t pt = sb + OFF_PT + w * (PT_CH_W * 4);
        const uint4 z = make_uint4(0, 0, 0, 0);
#pragma unroll 1
        for (int i = lane; i < (PT_CH_W - PT_L) / 4; i += 32) sts128(pt + 4 * PT_L + 16 * i, z);
        if (lane < 16) sts128(sb + OFF_XNF + w * XNF_CH + lane * 16, z);
    }
    kgen_tables(P, q, sb, w, half, lane);
    if (!half) conv_warp(P, sb, cta, w, lane);
    else help_warp(P, sb, cta, w, lane);
    y_exchange(P, sb, cta, threadIdx.x - 256);
}

}

extern "C" void kernel_launch(void* const* d_in, const int* in_sizes, int n_in, void* d_out, int out_size) {
    using namespace s4moe;
    (void)in_sizes; (void)n_in; (void)out_size;
    Params P;
    P.u = (const __nv_bfloat16*)d_in[0];
    P.A_re = (const __nv_bfloat16*)d_in[1];
    P.A_im = (const __nv_bfloat16*)d_in[2];
    P.B_re = (const __nv_bfloat16*)d_in[3];
    P.B_im = (const __nv_bfloat16*)d_in[4];
    P.C_re = (const __nv_bfloat16*)d_in[5];
    P.C_im = (const __nv_bfloat16*)d_in[6];
    P.log_dt = (const __nv_bfloat16*)d_in[7];
    P.Dskip = (const __nv_bfloat16*)d_in[8];
    P.w_r = (const __nv_bfloat16*)d_in[10];
    P.w_gate = (const __nv_bfloat16*)d_in[11];
    P.w_up = (const __nv_bfloat16*)d_in[12];
    P.w_down = (const __nv_bfloat16*)d_in[13];
    P.out = (__nv_bfloat16*)d_out;
    typedef CUresult (*EncodeFn)(CUtensorMap*, CUtensorMapDataType, cuuint32_t, void*, const cuuint64_t*, const cuuint64_t*,
                                 const cuuint32_t*, const cuuint32_t*, CUtensorMapInterleave, CUtensorMapSwizzle,
                                 CUtensorMapL2promotion, CUtensorMapFloatOOBfill);
    static EncodeFn encode = nullptr;
    static bool init = false;
    static void *p_rec, *p_hint, *p_xnT, *p_yT, *p_part, *p_dbg = nullptr, *p_dbgK = nullptr;
    if (!init) {
        init = true;
        cudaGetSymbolAddress(&p_rec, g_rec);
        cudaGetSymbolAddress(&p_hint, g_hint);
        cudaGetSymbolAddress(&p_xnT, g_xnT);
        cudaGetSymbolAddress(&p_yT, g_yT);
        cudaGetSymbolAddress(&p_part, g_part);
        void* fn = nullptr;
        cudaDriverEntryPointQueryResult qr;
        cudaGetDriverEntryPoint("cuTensorMapEncodeTiled", &fn, cudaEnableDefault, &qr);
        encode = (EncodeFn)fn;
        cudaFuncSetAttribute(fused_kernel, cudaFuncAttributeMaxDynamicSharedMemorySize, SMEM_BYTES);
    }
    CUtensorMap tmG, tmU;
    const cuuint64_t dims[2] = {(cuuint64_t)kF, (cuuint64_t)kD}, strides[1] = {(cuuint64_t)kF * 2};
    const cuuint32_t box[2] = {16, 256}, estr[2] = {1, 1};
    encode(&tmG, CU_TENSOR_MAP_DATA_TYPE_BFLOAT16, 2, d_in[11], dims, strides, box, estr, CU_TENSOR_MAP_INTERLEAVE_NONE,
           CU_TENSOR_MAP_SWIZZLE_NONE, CU_TENSOR_MAP_L2_PROMOTION_L2_128B, CU_TENSOR_MAP_FLOAT_OOB_FILL_NONE);
    encode(&tmU, CU_TENSOR_MAP_DATA_TYPE_BFLOAT16, 2, d_in[12], dims, strides, box, estr, CU_TENSOR_MAP_INTERLEAVE_NONE,
           CU_TENSOR_MAP_SWIZZLE_NONE, CU_TENSOR_MAP_L2_PROMOTION_L2_128B, CU_TENSOR_MAP_FLOAT_OOB_FILL_NONE);
    P.rec = (uint4*)p_rec; P.hint = (uint32_t*)p_hint; P.xnT = (uint4*)p_xnT; P.yT = (uint32_t*)p_yT; P.part = (uint32_t*)p_part;
    P.dbg = (long long*)p_dbg; P.dbgK = (float*)p_dbgK;
    fused_kernel<<<kCTA, kThreads, SMEM_BYTES>>>(P, tmG, tmU);
}
```

```cpp
#include <cuda.h>
#include <cuda_runtime.h>
#include <cuda_bf16.h>
#include <stdint.h>

#define DEVINL __device__ __forceinline__

namespace s4moe {

constexpr int kD = 512, kF = 1792;
constexpr int kCTA = 128, kThreads = 512, kFFN = 112;
constexpr int kSpin = 1 << 18;
#define GATHER_DELAY_NS 200
#define CLR_SLEEP_NS 100
#define FINAL_DELAY_NS 200

__device__ uint4 g_xnT[2 * 128 * 1024];
__device__ uint32_t g_yT[2 * 512 * 1024];
__device__ uint4 g_rec[2 * 128];
__device__ uint32_t g_hint[8 * 128];
__device__ uint32_t g_part[2 * kFFN * 512];
#define TS(i)
#define TG(i)
#define TDUMP()

constexpr int XNF_CH = (8 + 128) * 32;
constexpr int OFF_XNF = 0;
constexpr int OFF_OUT = OFF_XNF;
constexpr int PT0_W = 544, PTL_W = 48, PTH_W = 2 * 72, PTG_W = 2 * 92;
constexpr int PT_L = PT0_W, PT_H = PT_L + PTL_W, PT_G = PT_H + 4 * PTH_W, PT_CH_W = PT_G + 2 * PTG_W;
constexpr int OFF_PT = OFF_XNF + 4 * XNF_CH;
constexpr int KX_CH = 64 + 20 * 128 + 128 * 16;
constexpr int OFF_KX = OFF_PT + 4 * PT_CH_W * 4;
constexpr int OFF_YS = OFF_KX;
static_assert(4 * KX_CH >= 128 * 144, "y staging");
constexpr int MR_STR = 288, MR_EB = 128, MR_C128 = 256, MR_C2 = 264, MR_C1020 = 280, MR_WARP = 32 * MR_STR;
constexpr int KX_GEN = 64, KX_RAW = 64 + 20 * 128;
constexpr int OFF_MC = OFF_KX + 4 * KX_CH;
constexpr int WE2_P = 32, WE2_H = 113 * 16, WO2_P = 2, WO2_H = 98 * 16, W3_H = 64 * 16;
constexpr int WE2_O = 0, WO2_O = 2 * WE2_H, WO3_O = WO2_O + 2 * WO2_H, WE3_O = WO3_O + 2 * W3_H, W_CH = WE3_O + 2 * W3_H;
constexpr int OFF_W = OFF_MC;
constexpr int OFF_YT = OFF_W + 4 * W_CH;
static_assert(4 * W_CH + 16384 <= 8 * MR_WARP, "aliases of the mode tables");
constexpr int ROW = 1040;
constexpr int OFF_WG = (OFF_MC + 8 * MR_WARP + 127) / 128 * 128, OFF_WU = OFF_WG + 16384, OFF_WD = OFF_WU + 16384;
constexpr int OFF_XT = OFF_WD + 16 * ROW, OFF_XNT = OFF_XT + 16 * ROW;
constexpr int OFF_WR = OFF_XNT + 16 * ROW;
constexpr int OFF_DS = OFF_WR + 1024;
constexpr int OFF_XS = OFF_DS + 1024;
constexpr int OFF_STAT = OFF_XS + 1024;
constexpr int OFF_RP = OFF_STAT + 1024;
constexpr int OFF_FR = OFF_RP + 512;
constexpr int OFF_MS = OFF_FR + 1024;
constexpr int OFF_H = OFF_MS + 64;
constexpr int OFF_YR = OFF_H + 32;
constexpr int OFF_SEL = OFF_YR + 128;
constexpr int OFF_MBAR = OFF_SEL + 16;
constexpr int SMEM_BYTES = OFF_MBAR + 16;
static_assert(SMEM_BYTES <= 232448 - 1024, "shared memory");

enum { BAR_STAT = 1, BAR_R = 2, BAR_XN = 3, BAR_LN = 4, BAR_AUX = 5, BAR_Y = 6, BAR_YS = 12, BAR_GO = 13, BAR_FG = 14, BAR_R2 = 7, BAR_PAIR = 8   };

DEVINL void bar_sync(int id, int n) { asm volatile("bar.sync %0, %1;" ::"r"(id), "r"(n) : "memory"); }
DEVINL void bar_arrive(int id, int n) { asm volatile("bar.arrive %0, %1;" ::"r"(id), "r"(n) : "memory"); }

DEVINL uint32_t lds32(uint32_t a) { uint32_t v; asm volatile("ld.shared.u32 %0, [%1];" : "=r"(v) : "r"(a)); return v; }
DEVINL uint32_t lds16(uint32_t a) { unsigned short v; asm volatile("ld.shared.u16 %0, [%1];" : "=h"(v) : "r"(a)); return v; }
DEVINL float ldsf(uint32_t a) { float v; asm volatile("ld.shared.f32 %0, [%1];" : "=f"(v) : "r"(a)); return v; }
DEVINL uint2 lds64(uint32_t a) { uint2 v; asm volatile("ld.shared.v2.u32 {%0,%1}, [%2];" : "=r"(v.x), "=r"(v.y) : "r"(a)); return v; }
DEVINL float2 lds64f(uint32_t a) { float2 v; asm volatile("ld.shared.v2.f32 {%0,%1}, [%2];" : "=f"(v.x), "=f"(v.y) : "r"(a)); return v; }
DEVINL uint4 lds128(uint32_t a) { uint4 v; asm volatile("ld.shared.v4.u32 {%0,%1,%2,%3}, [%4];" : "=r"(v.x), "=r"(v.y), "=r"(v.z), "=r"(v.w) : "r"(a)); return v; }
DEVINL float4 lds128f(uint32_t a) { float4 v; asm volatile("ld.shared.v4.f32 {%0,%1,%2,%3}, [%4];" : "=f"(v.x), "=f"(v.y), "=f"(v.z), "=f"(v.w) : "r"(a)); return v; }
DEVINL void sts16(uint32_t a, uint32_t v) { asm volatile("st.shared.u16 [%0], %1;" ::"r"(a), "h"((unsigned short)v) : "memory"); }
DEVINL void sts32(uint32_t a, uint32_t v) { asm volatile("st.shared.u32 [%0], %1;" ::"r"(a), "r"(v) : "memory"); }
DEVINL void stsf(uint32_t a, float v) { asm volatile("st.shared.f32 [%0], %1;" ::"r"(a), "f"(v) : "memory"); }
DEVINL void sts64(uint32_t a, uint32_t x, uint32_t y) { asm volatile("st.shared.v2.u32 [%0], {%1,%2};" ::"r"(a), "r"(x), "r"(y) : "memory"); }
DEVINL void sts64f(uint32_t a, float x, float y) { asm volatile("st.shared.v2.f32 [%0], {%1,%2};" ::"r"(a), "f"(x), "f"(y) : "memory"); }
DEVINL void sts128(uint32_t a, uint4 v) { asm volatile("st.shared.v4.u32 [%0], {%1,%2,%3,%4};" ::"r"(a), "r"(v.x), "r"(v.y), "r"(v.z), "r"(v.w) : "memory"); }
DEVINL void sts128f(uint32_t a, float x, float y, float z, float w) { asm volatile("st.shared.v4.f32 [%0], {%1,%2,%3,%4};" ::"r"(a), "f"(x), "f"(y), "f"(z), "f"(w) : "memory"); }

DEVINL uint32_t ld_rlx32(const void* p) { uint32_t v; asm volatile("ld.relaxed.gpu.global.u32 %0, [%1];" : "=r"(v) : "l"(p) : "memory"); return v; }
DEVINL uint2 ld_rlx64(const void* p) { uint2 v; asm volatile("ld.relaxed.gpu.global.v2.u32 {%0,%1}, [%2];" : "=r"(v.x), "=r"(v.y) : "l"(p) : "memory"); return v; }
DEVINL uint4 ld_rlx128(const void* p) { uint4 v; asm volatile("ld.relaxed.gpu.global.v4.u32 {%0,%1,%2,%3}, [%4];" : "=r"(v.x), "=r"(v.y), "=r"(v.z), "=r"(v.w) : "l"(p) : "memory"); return v; }
DEVINL uint4 ld_acq128(const void* p) {
    uint4 v;
    asm volatile("ld.relaxed.gpu.global.v4.u32 {%0,%1,%2,%3}, [%4];" : "=r"(v.x), "=r"(v.y), "=r"(v.z), "=r"(v.w) : "l"(p) : "memory");
    return v;
}
DEVINL uint4 ld_weak128(const void* p) { uint4 v; asm volatile("ld.global.v4.u32 {%0,%1,%2,%3}, [%4];" : "=r"(v.x), "=r"(v.y), "=r"(v.z), "=r"(v.w) : "l"(p) : "memory"); return v; }
DEVINL uint32_t ld_nc32(const void* p) { uint32_t v; asm volatile("ld.global.nc.u32 %0, [%1];" : "=r"(v) : "l"(p)); return v; }
DEVINL uint32_t ld_nc16(const void* p) { unsigned short v; asm volatile("ld.global.nc.u16 %0, [%1];" : "=h"(v) : "l"(p)); return v; }
DEVINL uint32_t ld_weak32(const void* p) { uint32_t v; asm volatile("ld.global.u32 %0, [%1];" : "=r"(v) : "l"(p) : "memory"); return v; }
DEVINL void st_rlx8(void* p, uint32_t v) { asm volatile("st.relaxed.gpu.global.u8 [%0], %1;" ::"l"(p), "r"(v) : "memory"); }
DEVINL void st_rlx16(void* p, uint32_t v) { asm volatile("st.relaxed.gpu.global.u16 [%0], %1;" ::"l"(p), "h"((unsigned short)v) : "memory"); }
DEVINL void st_rlx32(void* p, uint32_t v) { asm volatile("st.relaxed.gpu.global.u32 [%0], %1;" ::"l"(p), "r"(v) : "memory"); }
DEVINL void st_rlx128(void* p, uint4 v) { asm volatile("st.relaxed.gpu.global.v4.u32 [%0], {%1,%2,%3,%4};" ::"l"(p), "r"(v.x), "r"(v.y), "r"(v.z), "r"(v.w) : "memory"); }
DEVINL void st_rlx64(void* p, uint32_t x, uint32_t y) { asm volatile("st.relaxed.gpu.global.v2.u32 [%0], {%1,%2};" ::"l"(p), "r"(x), "r"(y) : "memory"); }
DEVINL void cp_async16(uint32_t dst, const void* src) { asm volatile("cp.async.cg.shared.global [%0], [%1], 16;" ::"r"(dst), "l"(src) : "memory"); }
DEVINL void mbar_init(uint32_t a, uint32_t n) { asm volatile("mbarrier.init.shared::cta.b64 [%0], %1;" ::"r"(a), "r"(n) : "memory"); }
DEVINL void mbar_expect_tx(uint32_t a, uint32_t bytes) { asm volatile("mbarrier.arrive.expect_tx.shared::cta.b64 _, [%0], %1;" ::"r"(a), "r"(bytes) : "memory"); }
DEVINL bool mbar_try(uint32_t a, uint32_t parity) {
    uint32_t ok;
    asm volatile("{\n.reg .pred p;\nmbarrier.try_wait.parity.shared::cta.b64 p, [%1], %2, %3;\nselp.u32 %0, 1, 0, p;\n}" : "=r"(ok) : "r"(a), "r"(parity), "r"(4000) : "memory");
    return ok;
}
DEVINL void tma_2d(uint32_t dst, const CUtensorMap* tm, int x, int y, uint32_t mbar) {
    asm volatile("cp.async.bulk.tensor.2d.shared::cluster.global.mbarrier::complete_tx::bytes [%0], [%1, {%3, %4}], [%2];"
                 ::"r"(dst), "l"(tm), "r"(mbar), "r"(x), "r"(y) : "memory");
}
DEVINL void tma_1d(uint32_t dst, const void* src, uint32_t bytes, uint32_t mbar) {
    asm volatile("cp.async.bulk.shared::cluster.global.mbarrier::complete_tx::bytes [%0], [%1], %2, [%3];"
                 ::"r"(dst), "l"(src), "r"(bytes), "r"(mbar) : "memory");
}
DEVINL void tma_store_1d(void* dst, uint32_t src, uint32_t bytes) {
    asm volatile("cp.async.bulk.global.shared::cta.bulk_group [%0], [%1], %2;" ::"l"(dst), "r"(src), "r"(bytes) : "memory");
}

DEVINL void mma_bf16(float* d, uint32_t a0, uint32_t a1, uint32_t a2, uint32_t a3, uint32_t b0, uint32_t b1) {
    asm volatile("mma.sync.aligned.m16n8k16.row.col.f32.bf16.bf16.f32 {%0,%1,%2,%3}, {%4,%5,%6,%7}, {%8,%9}, {%0,%1,%2,%3};"
                 : "+f"(d[0]), "+f"(d[1]), "+f"(d[2]), "+f"(d[3])
                 : "r"(a0), "r"(a1), "r"(a2), "r"(a3), "r"(b0), "r"(b1));
}
DEVINL void mma_f16(float* d, uint32_t a0, uint32_t a1, uint32_t a2, uint32_t a3, uint32_t b0, uint32_t b1) {
    asm volatile("mma.sync.aligned.m16n8k16.row.col.f32.f16.f16.f32 {%0,%1,%2,%3}, {%4,%5,%6,%7}, {%8,%9}, {%0,%1,%2,%3};"
        : "+f"(d[0]), "+f"(d[1]), "+f"(d[2]), "+f"(d[3])
        : "r"(a0), "r"(a1), "r"(a2), "r"(a3), "r"(b0), "r"(b1));
}
DEVINL void ldsm_x4(uint32_t& r0, uint32_t& r1, uint32_t& r2, uint32_t& r3, uint32_t a) {
    asm volatile("ldmatrix.sync.aligned.m8n8.x4.shared.b16 {%0,%1,%2,%3}, [%4];" : "=r"(r0), "=r"(r1), "=r"(r2), "=r"(r3) : "r"(a));
}
DEVINL void ldsm_x4_t(uint32_t& r0, uint32_t& r1, uint32_t& r2, uint32_t& r3, uint32_t a) {
    asm volatile("ldmatrix.sync.aligned.m8n8.x4.trans.shared.b16 {%0,%1,%2,%3}, [%4];" : "=r"(r0), "=r"(r1), "=r"(r2), "=r"(r3) : "r"(a));
}
DEVINL void stsm_x4(uint32_t a, uint32_t r0, uint32_t r1, uint32_t r2, uint32_t r3) {
    asm volatile("stmatrix.sync.aligned.m8n8.x4.shared.b16 [%0], {%1,%2,%3,%4};" ::"r"(a), "r"(r0), "r"(r1), "r"(r2), "r"(r3) : "memory");
}
DEVINL uint32_t movm(uint32_t a) { uint32_t d; asm volatile("movmatrix.sync.aligned.m8n8.trans.b16 %0, %1;" : "=r"(d) : "r"(a)); return d; }
DEVINL uint32_t pack_bf16(float lo, float hi) { uint32_t d; asm("cvt.rn.bf16x2.f32 %0, %1, %2;" : "=r"(d) : "f"(hi), "f"(lo)); return d; }
DEVINL uint32_t pack_f16(float lo, float hi) { uint32_t d; asm("cvt.rn.f16x2.f32 %0, %1, %2;" : "=r"(d) : "f"(hi), "f"(lo)); return d; }
DEVINL float bf_lo(uint32_t w) { return __uint_as_float(w << 16); }
DEVINL float bf_hi(uint32_t w) { return __uint_as_float(w & 0xffff0000u); }
DEVINL float bf_round(float x) { return bf_lo(pack_bf16(x, 0.f)); }
DEVINL uint32_t bsub2(uint32_t a, uint32_t b) { uint32_t d; asm("sub.rn.bf16x2 %0, %1, %2;" : "=r"(d) : "r"(a), "r"(b)); return d; }
DEVINL uint32_t badd2(uint32_t a, uint32_t b) { uint32_t d; asm("add.rn.bf16x2 %0, %1, %2;" : "=r"(d) : "r"(a), "r"(b)); return d; }
DEVINL uint32_t bmul2(uint32_t a, uint32_t b) { uint32_t d; asm("mul.rn.bf16x2 %0, %1, %2;" : "=r"(d) : "r"(a), "r"(b)); return d; }
DEVINL uint32_t hmul2(uint32_t a, uint32_t b) { uint32_t d; asm("mul.rn.f16x2 %0, %1, %2;" : "=r"(d) : "r"(a), "r"(b)); return d; }
DEVINL uint32_t hfma2(uint32_t a, uint32_t b, uint32_t c) { uint32_t d; asm("fma.rn.f16x2 %0, %1, %2, %3;" : "=r"(d) : "r"(a), "r"(b), "r"(c)); return d; }
DEVINL uint32_t hneg2(uint32_t a) { uint32_t d; asm("neg.f16x2 %0, %1;" : "=r"(d) : "r"(a)); return d; }
DEVINL float ex2f(float x) { float y; asm("ex2.approx.ftz.f32 %0, %1;" : "=f"(y) : "f"(x)); return y; }
DEVINL float rcpaf(float x) { float y; asm("rcp.approx.ftz.f32 %0, %1;" : "=f"(y) : "f"(x)); return y; }
DEVINL float sqrtaf(float x) { float y; asm("sqrt.approx.ftz.f32 %0, %1;" : "=f"(y) : "f"(x)); return y; }
DEVINL float sinaf(float x) { float y; asm("sin.approx.ftz.f32 %0, %1;" : "=f"(y) : "f"(x)); return y; }
DEVINL float cosaf(float x) { float y; asm("cos.approx.ftz.f32 %0, %1;" : "=f"(y) : "f"(x)); return y; }
DEVINL uint32_t norm2(uint32_t x, uint32_t m2, float rs) { const uint32_t d = bsub2(x, m2); return pack_bf16(bf_lo(d) * rs, bf_hi(d) * rs); }

struct cf { float r, i; };
DEVINL cf cmul(cf a, cf b) { return {fmaf(a.r, b.r, -a.i * b.i), fmaf(a.r, b.i, a.i * b.r)}; }
DEVINL cf cmulc(cf a, cf b) { return {fmaf(a.r, b.r, a.i * b.i), fmaf(a.i, b.r, -a.r * b.i)}; }
DEVINL cf csq(cf a) { return {fmaf(a.r, a.r, -a.i * a.i), (a.r + a.r) * a.i}; }
DEVINL cf cexpx(float alpha, float beta, float x) {
    const float m = ex2f(alpha * x), th = beta * x;
    return {m * cosaf(th), m * sinaf(th)};
}
struct ch2 { uint32_t r, i; };
DEVINL ch2 pk(cf a, cf b) { return {pack_f16(a.r, b.r), pack_f16(a.i, b.i)}; }
DEVINL ch2 hcmul(ch2 a, ch2 b) { return {hfma2(a.r, b.r, hneg2(hmul2(a.i, b.i))), hfma2(a.r, b.i, hmul2(a.i, b.r))}; }
DEVINL ch2 hcmulc(ch2 a, ch2 b) { return {hfma2(a.r, b.r, hmul2(a.i, b.i)), hfma2(a.i, b.r, hneg2(hmul2(a.r, b.i)))}; }

struct Params {
    const __nv_bfloat16 *u, *w_r, *Dskip;
    uint4* rec;
    uint32_t* hint;
    const __nv_bfloat16 *A_re, *A_im, *B_re, *B_im, *C_re, *C_im, *log_dt;
    uint4* xnT;
    uint32_t* yT;
    uint32_t* part;
    const __nv_bfloat16 *w_gate, *w_up, *w_down;
    __nv_bfloat16* out;
    long long* dbg;
    float* dbgK;
};

__device__ __noinline__ void kgen_generic(uint32_t raw, uint32_t out, int t0, int nt, int lane) {
    const int g = lane >> 2, c = lane & 3;
#pragma unroll 1
    for (int q = 0; q < 4 * nt; q++) {
        const int t = t0 + (q >> 2), r = q & 3, j = g + 8 * (r >> 1), i = 2 * c + (r & 1);
        const int x = t == 0 ? i : t == 1 ? 128 + i : t == 2 ? ((i & 1) ? 383 + i : 256 + i)
                    : t == 3 ? (i < 4 ? 512 + 128 * i : 128 * i + 4) : 1024 + 128 * i;
        const float l = (float)(8 * j + x);
        float s = 0.f;
#pragma unroll 1
        for (int n = 0; n < 128; n++) {
            const float4 m = lds128f(raw + 16 * n);
            const float th = m.y * l;
            s += ex2f(m.x * l) * (m.z * cosaf(th) - m.w * sinaf(th));
        }
        stsf(out + q * 128 + lane * 4, s);
    }
}

struct ModeRegs { uint32_t ar, ai, br, bi, cr, ci, ldt; };
DEVINL void kgen_tables(const Params& P, const ModeRegs& q, uint32_t sb, int w, int half, int lane) {
    const uint32_t qar = q.ar, qai = q.ai, qbr = q.br, qbi = q.bi, qcr = q.cr, qci = q.ci;
    const float dt = bf_round(expf(bf_lo(q.ldt)));
    const uint32_t mr = sb + OFF_MC + (2 * w + half) * MR_WARP, kx = sb + OFF_KX + w * KX_CH + half * 16;
    TS(14);
    const float al0 = (dt * bf_lo(qar)) * 1.4426950408889634f, al1 = (dt * bf_hi(qar)) * 1.4426950408889634f;
    const float be0 = dt * bf_lo(qai), be1 = dt * bf_hi(qai);
    const cf c0 = cmul(cf{bf_lo(qcr), bf_lo(qci)}, cf{dt * bf_lo(qbr), dt * bf_lo(qbi)});
    const cf c1 = cmul(cf{bf_hi(qcr), bf_hi(qci)}, cf{dt * bf_hi(qbr), dt * bf_hi(qbi)});
    const uint32_t ex = min(__reduce_max_sync(0xffffffffu, __float_as_uint(fmaxf(fmaxf(fabsf(c0.r), fabsf(c0.i)), fmaxf(fabsf(c1.r), fabsf(c1.i))))) >> 23, 253u);
    const float scl = __uint_as_float((254u - ex) << 23), unscl = __uint_as_float(ex << 23);
    const bool grow = __any_sync(0xffffffffu, al0 > 0.f || al1 > 0.f);
    const uint32_t a = mr + lane * MR_STR;
    {
        const cf e1a = cexpx(al0, be0, 1.f), e1b = cexpx(al1, be1, 1.f), e8a = cexpx(al0, be0, 8.f), e8b = cexpx(al1, be1, 8.f);
        const cf e64a = cexpx(al0, be0, 64.f), e64b = cexpx(al1, be1, 64.f);
        const cf e2a = csq(e1a), e2b = csq(e1b), e16a = csq(e8a), e16b = csq(e8b);
        const cf e128a = csq(e64a), e128b = csq(e64b), e256a = csq(e128a), e256b = csq(e128b), e512a = csq(e256a), e512b = csq(e256b);
        const ch2 H1 = pk(e1a, e1b), H2 = pk(e2a, e2b), H4 = pk(csq(e2a), csq(e2b)), H8 = pk(e8a, e8b), H16 = pk(e16a, e16b);
        const ch2 H32 = pk(csq(e16a), csq(e16b)), H64 = pk(e64a, e64b), H128 = pk(e128a, e128b), H256 = pk(e256a, e256b), H512 = pk(e512a, e512b);
        const ch2 H383 = pk(cexpx(al0, be0, 383.f), cexpx(al1, be1, 383.f)), H1020 = pk(cexpx(al0, be0, 1020.f), cexpx(al1, be1, 1020.f));
        const cf ta = csq(csq(e512a)), tb = csq(csq(e512b));
        float k2048 = fmaf(c0.r, ta.r, -c0.i * ta.i) + fmaf(c1.r, tb.r, -c1.i * tb.i);
        ch2 L[4], M[4], Q[4];
        L[0] = ch2{0x3c003c00u, 0u}; L[1] = H1; L[2] = H2; L[3] = hcmul(H1, H2);
        M[0] = pk(cf{c0.r * scl, -c0.i * scl}, cf{c1.r * scl, -c1.i * scl});
        M[1] = hcmulc(M[0], H8); M[2] = hcmulc(M[0], H16); M[3] = hcmulc(M[1], H16);
        Q[0] = H512; Q[1] = hcmul(H512, H128); Q[2] = hcmul(H512, H256); Q[3] = hcmul(Q[1], H256);
        const uint32_t sa = 16 * ((lane >> 2) & 1);
#pragma unroll
        for (int b = 0; b < 4; b++) {
            const ch2 lu = hcmul(L[b], H4), mu = hcmulc(M[b], H32), qu = hcmul(Q[b], H4);
            const ch2 m2 = hcmulc(M[b], H64), mu2 = hcmulc(mu, H64);
            sts128(a + ((16 * b) ^ sa), make_uint4(M[b].r, m2.r, M[b].i, m2.i));
            sts128(a + 64 + ((16 * b) ^ sa), make_uint4(mu.r, mu2.r, mu.i, mu2.i));
            sts128(a + MR_EB + ((16 * b) ^ sa), make_uint4(L[b].r, L[b].i, Q[b].r, Q[b].i));
            sts128(a + MR_EB + 64 + ((16 * b) ^ sa), make_uint4(lu.r, lu.i, qu.r, qu.i));
        }
        sts128(a + MR_C128, make_uint4(H128.r, H128.i, H256.r, H256.i));
        sts128(a + MR_C128 + 16, make_uint4(H383.r, H383.i, H1020.r, H1020.i));
#pragma unroll
        for (int o = 16; o; o >>= 1) k2048 += __shfl_xor_sync(0xffffffffu, k2048, o);
        if (lane == 0) sts128f(kx, k2048, unscl, grow ? 1.f : 0.f, 0.f);
        {
            const uint32_t raw = sb + OFF_KX + w * KX_CH + KX_RAW + (64 * half + 2 * lane) * 16;
            sts128f(raw, al0, be0, c0.r, c0.i);
            sts128f(raw + 16, al1, be1, c1.r, c1.i);
        }
    }
    if (half && lane == 0 && w < 3) {
        const __nv_bfloat16* wp = w == 0 ? P.w_gate : w == 1 ? P.w_up : P.w_down;
        asm volatile("cp.async.bulk.prefetch.L2.global [%0], %1;" ::"l"(wp + (size_t)blockIdx.x * 7168), "r"(14336) : "memory");
    }
    TS(1);
    bar_sync(BAR_PAIR + w, 64);
}

template <int T0, int NT>
DEVINL void kgen_eval(uint32_t sb, int w, int lane, float (&kd)[NT][4]) {
    const int g = lane >> 2, c = lane & 3;
    const uint32_t mr = sb + OFF_MC + 2 * w * MR_WARP, kx = sb + OFF_KX + w * KX_CH;
    const float4 s0 = lds128f(kx), s1 = lds128f(kx + 16);
    if (s0.z == 0.f && s1.z == 0.f) {
        float tot[NT][4];
#pragma unroll 1
        for (int h = 0; h < 2; h++) {
#pragma unroll
            for (int t = 0; t < NT; t++) { kd[t][0] = kd[t][1] = kd[t][2] = kd[t][3] = 0.f; }
            const uint32_t p0 = mr + h * MR_WARP + c * MR_STR;
#pragma unroll 4
            for (int s = 0; s < 8; s++) {
                const uint32_t p = p0 + s * (4 * MR_STR);
                const uint4 A = lds128(p + 16 * (g ^ (s & 1)));
                const uint32_t pb = p + MR_EB + 16 * (g ^ (s & 1));
                if (T0 == 0) {
                    const uint2 l = lds64(pb), c1 = lds64(p + MR_C128), c2 = lds64(p + MR_C2 + 8 * (g & 1));
                    const ch2 w0 = {l.x, l.y};
                    const ch2 w1 = hcmul(w0, ch2{c1.x, c1.y}), w2 = hcmul(w0, ch2{c2.x, c2.y});
                    mma_f16(kd[0], A.x, A.y, A.z, A.w, w0.r, w0.i);
                    mma_f16(kd[1], A.x, A.y, A.z, A.w, w1.r, w1.i);
                    mma_f16(kd[NT - 1], A.x, A.y, A.z, A.w, w2.r, w2.i);
                } else {
                    const uint2 q = lds64(pb + 8), c4 = lds64(g < 4 ? p + MR_EB + 16 * (s & 1) + 8 : p + MR_C1020);
                    const ch2 w3 = {q.x, q.y};
                    const ch2 w4 = hcmul(w3, ch2{c4.x, c4.y});
                    mma_f16(kd[0], A.x, A.y, A.z, A.w, w3.r, w3.i);
                    mma_f16(kd[1], A.x, A.y, A.z, A.w, w4.r, w4.i);
                }
            }
            const float u = h ? s1.y : s0.y;
#pragma unroll
            for (int t = 0; t < NT; t++)
#pragma unroll
                for (int r = 0; r < 4; r++) { kd[t][r] = h ? fmaf(kd[t][r], u, tot[t][r]) : kd[t][r] * u; tot[t][r] = kd[t][r]; }
        }
    } else {
        const uint32_t st = kx + KX_GEN + (T0 ? 12 * 128 : 0);
        kgen_generic(kx + KX_RAW, st, T0, NT, lane);
        __syncwarp();
#pragma unroll
        for (int q = 0; q < 4 * NT; q++) kd[q >> 2][q & 3] = ldsf(st + q * 128 + lane * 4);
    }
}

DEVINL void conv_warp(const Params& P, uint32_t sb, int cta, int w, int lane) {
    const int g = lane >> 2, c = lane & 3;
    const uint32_t kx = sb + OFF_KX + w * KX_CH, pt = sb + OFF_PT + w * (PT_CH_W * 4);
    float kd[3][4];
    kgen_eval<0, 3>(sb, w, lane, kd);
    TS(2);
    float k510;
    {
        const uint32_t p0 = pt + 64 + 8 * lane;
        const int lm1 = (lane + 31) & 31, lp1 = (lane + 1) & 31;
        float rot[4], pv[4], nx[4];
        const float e[4] = {kd[2][0], kd[2][2], kd[2][1], kd[2][3]};
#pragma unroll
        for (int s = 0; s < 4; s++) {
            rot[s] = __shfl_sync(0xffffffffu, kd[s >> 1][2 * (s & 1) + 1], lm1);
            pv[s] = __shfl_sync(0xffffffffu, e[s], lm1);
            nx[s] = __shfl_sync(0xffffffffu, e[s], lp1);
        }
        const bool odd = lane & 1;
#pragma unroll
        for (int s = 0; s < 4; s++) {
            const float v0 = kd[s >> 1][2 * (s & 1)], v1 = kd[s >> 1][2 * (s & 1) + 1];
            const float prev = lane ? rot[s] : (s ? rot[s > 0 ? s - 1 : 0] : 0.f);
            sts64(p0 + 256 * s, pack_bf16(v0, prev), pack_bf16(v1, v0));
            const float nn = lane == 31 ? nx[s < 3 ? s + 1 : 3] : nx[s];
            const float lo = odd ? pv[s] : ((s == 0 && lane == 0) ? rot[3] : e[s]);
            sts64(p0 + 1024 + 256 * s, pack_bf16(e[s], lo), pack_bf16(odd ? nn : e[s], e[s]));
        }
        if (lane < 16) { sts32(pt + 4 * lane, 0u); sts32(pt + 4 * (528 + lane), 0u); }
        k510 = e[3];
        const float k508 = pv[3];
        TS(3);
        bar_sync(BAR_XN, kThreads);
        TS(4);
        if (lane == 31) {
            const float d = k510 - ldsf(kx + 32);
            sts64(p0 + 1024 + 256 * 3, pack_bf16(d, k508), pack_bf16(0.f, d));
        }
        __syncwarp();
    }
    float acc[16][4];
#pragma unroll
    for (int j = 0; j < 16; j++) { acc[j][0] = acc[j][1] = acc[j][2] = acc[j][3] = 0.f; }
    const int x0 = g - 2 * c;
    const uint32_t ptx = pt + 4 * (16 + x0);
    const uint32_t xb = sb + OFF_XNF + w * XNF_CH + (8 + g) * 32 + 8 * c;
    {
        uint32_t A[4][4];
#pragma unroll
        for (int dp = 0; dp < 4; dp++) {
            const uint32_t b = ptx + 512 * dp;
            A[dp][0] = lds32(b); A[dp][1] = lds32(b + 32); A[dp][2] = lds32(b - 32); A[dp][3] = A[dp][0];
        }
        {
            const uint32_t b = ptx + 64 * 32;
            const uint32_t a0 = lds32(b), a1 = lds32(b + 32), a2 = lds32(b - 32);
#pragma unroll
            for (int tau = 0; tau < 12; tau++) {
                const uint2 B = lds64(xb + tau * 256);
                mma_bf16(acc[tau + 4], a0, a1, a2, a0, B.x, B.y);
            }
        }
        uint32_t xr = xb, pr = ptx;
        uint2 Bn = lds64(xr), Bn2 = lds64(xr + 256);
#pragma unroll 1
        for (int rho = 0; rho < 8; rho++, xr -= 32) {
            pr += 64;
#pragma unroll
            for (int tau = 0; tau < 16; tau++) {
                const uint2 B = Bn;
                Bn = Bn2;
                Bn2 = tau < 14 ? lds64(xr + (tau + 2) * 256) : lds64(xr - 32 + (tau - 14) * 256);
#pragma unroll
                for (int dp = 3; dp >= 0; dp--)
                    if (tau + dp < 16) mma_bf16(acc[tau + dp], A[dp][0], A[dp][1], A[dp][2], A[dp][3], B.x, B.y);
                if (tau >= 12) {
                    const int dp = 15 - tau;
                    const uint32_t b = pr + 512 * dp;
                    A[dp][0] = lds32(b); A[dp][1] = lds32(b + 32); A[dp][2] = lds32(b - 32); A[dp][3] = lds32(b);
                }
            }
        }
    }
    TS(5);
    bar_sync(BAR_PAIR + w, 64);
    TS(6);
#pragma unroll
    for (int rho = 0; rho < 2; rho++) {
        const uint32_t b = ptx + 4 * PT_L + 64 * rho;
        const uint32_t a0 = lds32(b), a1 = lds32(b + 32), a2 = lds32(b - 32);
#pragma unroll
        for (int tau = 0; tau < 8; tau++) {
            const uint2 B = lds64(xb - rho * 32 + tau * 256);
            mma_bf16(acc[tau + 8], a0, a1, a2, a0, B.x, B.y);
        }
    }
    {
        const uint32_t wb = sb + OFF_W + w * W_CH;
        const int hp = (lane >> 3) & 1, row = 8 * (lane >> 4) + (lane & 7);
        uint2 tb[8];
        uint32_t aw = 0;
#pragma unroll
        for (int h = 0; h < 4; h++) {
            const int q = hp + ((h & 1) ? WE2_P : WO2_P) + (h == 2 ? -1 : h == 3 ? 1 : 0);
            aw = wb + ((h & 1) ? WE2_O + (q & 1) * WE2_H : WO2_O + (q & 1) * WO2_H) + (row + (q >> 1)) * 16;
            const uint32_t tp = pt + 4 * (PT_H + h * PTH_W) + 8 * (16 + x0);
#pragma unroll
            for (int i = 0; i < 6; i++) tb[i] = lds64(tp + 64 * i);
#pragma unroll
            for (int kap = 0; kap < 6; kap++) {
                uint32_t a0, a1, a2, a3;
                ldsm_x4_t(a0, a1, a2, a3, aw + 256 * kap);
#pragma unroll
                for (int d = 0; d < 6; d++)
                    if (4 + 2 * kap + d < 16) mma_bf16(acc[4 + 2 * kap + d], a0, a1, a2, a3, tb[d].x, tb[d].y);
            }
        }
        {
            uint32_t a0, a1, a2, a3;
            ldsm_x4_t(a0, a1, a2, a3, aw - 256);
#pragma unroll
            for (int d = 1; d < 6; d++) mma_bf16(acc[2 + d], a0, a1, a2, a3, tb[d].x, tb[d].y);
        }
#pragma unroll
        for (int gp = 0; gp < 2; gp++) {
            const uint32_t aw3 = wb + (gp ? WE3_O : WO3_O) + hp * W3_H + row * 16;
            const uint32_t tp = pt + 4 * (PT_G + gp * PTG_W) + 8 * (16 + x0);
#pragma unroll
            for (int i = 0; i < 8; i++) tb[i] = lds64(tp + 64 * i);
#pragma unroll
            for (int kap = 0; kap < 4; kap++) {
                uint32_t a0, a1, a2, a3;
                ldsm_x4_t(a0, a1, a2, a3, aw3 + 256 * kap);
#pragma unroll
                for (int d = 0; d < 8; d++)
                    if (8 + 2 * kap + d < 16) mma_bf16(acc[8 + 2 * kap + d], a0, a1, a2, a3, tb[d].x, tb[d].y);
            }
        }
    }
    TS(7);
    if (w == 0 && lane < 8) st_rlx8((uint8_t*)(P.hint + lane * 128 + cta) + 3, lds32(sb + OFF_SEL + 8));
    {
        const uint32_t ys = sb + OFF_YS + (2 * c * 36 + 8 * w + g) * 4;
#pragma unroll
        for (int j = 0; j < 16; j++) {
            sts32(ys + j * (8 * 144), ~pack_bf16(acc[j][0], acc[j][2]));
            sts32(ys + j * (8 * 144) + 144, ~pack_bf16(acc[j][1], acc[j][3]));
        }
    }
    TS(8);
}

DEVINL void y_exchange(const Params& P, uint32_t sb, int cta, int t) {
    bar_sync(BAR_YS, 256);
    const uint32_t tag = lds32(sb + OFF_SEL + 8);
    uint4* base = (uint4*)P.yT + (size_t)(tag & 1) * (128 * 1024);
#pragma unroll
    for (int r = 0; r < 4; r++) {
        const int u = t + 256 * r;
        st_rlx128(base + (size_t)(u >> 3) * 1024 + cta * 8 + (u & 7), lds128(sb + OFF_YS + (u >> 3) * 144 + (u & 7) * 16));
    }
    TS(10);
    if (t >= 224) {
#pragma unroll 1
        for (int it = 0; it < kSpin; it++) {
            const uint4 h = ld_rlx128(P.hint + (cta & 7) * 128 + 4 * (t - 224));
            const uint32_t t8 = tag << 24;
            if (__all_sync(0xffffffffu, (((h.x ^ t8) | (h.y ^ t8) | (h.z ^ t8) | (h.w ^ t8)) >> 24) == 0)) break;
        }
    }
    bar_sync(BAR_YS, 256);
    TS(12);
    const uint4* src = base + (size_t)cta * 1024 + t;
    uint4 v[4];
#pragma unroll
    for (int r = 0; r < 4; r++) v[r] = ld_weak128(src + 256 * r);
#pragma unroll 1
    for (int it = 0; it < kSpin; it++) {
        bool ok = true;
#pragma unroll
        for (int r = 0; r < 4; r++) ok = ok && v[r].x != 0u && v[r].y != 0u && v[r].z != 0u && v[r].w != 0u;
        if (__all_sync(0xffffffffu, ok)) break;
#pragma unroll
        for (int r = 0; r < 4; r++) if (v[r].x == 0u || v[r].y == 0u || v[r].z == 0u || v[r].w == 0u) v[r] = ld_rlx128(src + 256 * r);
    }
#pragma unroll
    for (int r = 0; r < 4; r++) sts128(sb + OFF_YT + (t + 256 * r) * 16, v[r]);
    bar_arrive(BAR_Y, kThreads);
    TS(11); TDUMP();
}

DEVINL void help_warp(const Params& P, uint32_t sb, int cta, int w, int lane) {
    const int g = lane >> 2, c = lane & 3;
    const uint32_t kx = sb + OFF_KX + w * KX_CH, pt = sb + OFF_PT + w * (PT_CH_W * 4);
    float kd[2][4];
    kgen_eval<3, 2>(sb, w, lane, kd);
    TS(2);
    {
        if (lane == 0) stsf(kx + 32, kd[0][0]);
        auto put = [](uint32_t a, uint32_t v) { sts16(a, v); sts16(a + 10, v); sts16(a + 68, v); sts16(a + 78, v); };
        const int h = ((c >> 1) + 2 * (g & 1) + 3) & 3, gp = (g & 1) ^ 1;
        const uint32_t a3 = pt + 4 * (PT_H + h * PTH_W) + 8 * (16 + 16 * (c & 1) + (g >> 1));
        const uint32_t a4 = pt + 4 * (PT_G + gp * PTG_W) + 8 * (16 + 16 * c + (g >> 1) - gp);
#pragma unroll
        for (int q = 0; q < 8; q++) {
            const int r = q & 3;
            const uint32_t a = ((q >> 2) ? a4 : a3) + 8 * (8 * (r & 1) + 4 * (r >> 1));
            put((q == 4 && lane == 0) ? pt + 4 * (PT_H + 3 * PTH_W) + 8 * (16 + 32) : a, pack_bf16(kd[q >> 2][r], 0.f));
        }
        if (lane == 0) {
            const uint32_t v = pack_bf16(kd[1][0], 0.f), al = pt + 4 * (PT_L + 16 + 3);
            sts16(al, v); sts16(al + 4, v); sts16(al + 6, v); sts16(al + 10, v);
            put(pt + 4 * (PT_G + PTG_W) + 8 * (16 + 63), pack_bf16(ldsf(kx) + ldsf(kx + 16), 0.f));
        }
    }
    TS(3);
    bar_sync(BAR_XN, kThreads);
    TS(4);
    const uint32_t wb = sb + OFF_W + w * W_CH;
    {
        const uint4 z = make_uint4(0, 0, 0, 0);
        sts128(wb + WE2_O + (lane & 1) * WE2_H + (lane >> 1) * 16, z);
        if (lane < 2) sts128(wb + WO2_O + lane * WO2_H, z);
    }
#pragma unroll 1
    for (int b = lane; b < 96; b += 32) {
        const uint32_t xa = sb + OFF_XNF + w * XNF_CH + (8 + b - 2) * 32;
        const uint4 p1 = lds128(xa + 16);
        const uint4 q0 = lds128(xa + 32), q1 = lds128(xa + 48);
        const uint4 r0 = lds128(xa + 64), r1 = lds128(xa + 80);
        const uint32_t u[17] = {p1.y, p1.w, q0.x, q0.z, q1.x, q1.z, q0.y, q0.w, q1.y, q1.w, r0.x, r0.z, r1.x, r1.z, r0.y, r0.w, r1.y};
        float C[34];
        C[0] = 0.f;
#pragma unroll
        for (int i = 0; i < 33; i++) C[i + 1] = C[i] + ((i & 1) ? bf_hi(u[i >> 1]) : bf_lo(u[i >> 1]));
#pragma unroll
        for (int hh = 0; hh < 2; hh++) {
            uint32_t o2[4], e2[4];
#pragma unroll
            for (int i = 0; i < 4; i++) {
                const int t = 8 * hh + 2 * i;
                o2[i] = pack_bf16(C[t + 18] - C[t + 15], C[t + 19] - C[t + 16]);
                e2[i] = pack_bf16(C[t + 15] - C[t + 10], C[t + 16] - C[t + 11]);
            }
            sts128(wb + b * 16 + WO2_O + hh * WO2_H + (WO2_P / 2) * 16, make_uint4(o2[0], o2[1], o2[2], o2[3]));
            sts128(wb + b * 16 + WE2_O + hh * WE2_H + (WE2_P / 2) * 16, make_uint4(e2[0], e2[1], e2[2], e2[3]));
        }
        if (b < 64) {
#pragma unroll
            for (int hh = 0; hh < 2; hh++) {
                uint32_t o3[4], e3[4];
#pragma unroll
                for (int i = 0; i < 4; i++) {
                    const int t = 8 * hh + 2 * i;
                    o3[i] = pack_bf16(C[t + 16] - C[t + 9], C[t + 17] - C[t + 10]);
                    e3[i] = pack_bf16(C[t + 9] - C[t + 0], C[t + 10] - C[t + 1]);
                }
                sts128(wb + b * 16 + WO3_O + hh * W3_H, make_uint4(o3[0], o3[1], o3[2], o3[3]));
                sts128(wb + b * 16 + WE3_O + hh * W3_H, make_uint4(e3[0], e3[1], e3[2], e3[3]));
            }
        }
    }
    if (lane < 8) {
        float s = 0.f;
#pragma unroll 1
        for (int j = 6; j <= 10; j++) {
            const int t = 1536 + lane - j, p = t & 15;
            s += __uint_as_float(lds16(sb + OFF_XNF + w * XNF_CH + (8 + (t >> 4)) * 32 + 8 * ((p & 7) >> 1) + 4 * (p >> 3) + 2 * (p & 1)) << 16);
        }
        sts16(wb + WE2_O + (96 + WE2_P / 2) * 16 + 2 * lane, pack_bf16(s, 0.f));
    }
    bar_arrive(BAR_PAIR + w, 64);
    TS(5);
    {
        const uint32_t tag = lds32(sb + OFF_SEL + 8);
        uint4* zy = (uint4*)P.yT + (size_t)((tag & 1) ^ 1) * (128 * 1024) + (size_t)cta * 1024 + 32 * w + lane;
#pragma unroll 1
        for (int r = 0; r < 8; r++) { zy[128 * r] = make_uint4(0, 0, 0, 0); __nanosleep(CLR_SLEEP_NS); }
    }
}

extern __shared__ __align__(128) unsigned char smem_generic[];
DEVINL void aux_warp(const Params& P, const CUtensorMap* tmG, const CUtensorMap* tmU, uint32_t sb, int cta, int hw, int lane, uint32_t prev_rec) {
    const int g = lane >> 2, c = lane & 3;
    const int tid = hw * 32 + lane;
    uint32_t* const rec = (uint32_t*)&P.rec[2 * cta];
    const uint32_t tag = (prev_rec + 1u) & 0xffffu;
    if (tid == 0) {
        mbar_init(sb + OFF_MBAR, 1);
        asm volatile("fence.mbarrier_init.release.cluster;\nfence.proxy.async.shared::cta;" ::: "memory");
    }
    asm volatile("cp.async.wait_group 0;" ::: "memory");
    TS(5);
    bar_sync(BAR_STAT, 256);
    const uint32_t ta = ((lane & 7) + 8 * ((lane >> 3) & 1)) * ROW + (64 * hw + 8 * (lane >> 4)) * 2;
    uint32_t xa[4][4];
#pragma unroll
    for (int k = 0; k < 4; k++) ldsm_x4(xa[k][0], xa[k][1], xa[k][2], xa[k][3], sb + OFF_XT + ta + 32 * k);
    {
        float aS[4] = {0, 0, 0, 0}, aG0[4] = {0, 0, 0, 0}, aG1[4] = {0, 0, 0, 0};
#pragma unroll
        for (int k = 0; k < 4; k++) {
            mma_bf16(aS, xa[k][0], xa[k][1], xa[k][2], xa[k][3], 0x3f803f80u, 0x3f803f80u);
            mma_bf16(aG0, xa[k][0], xa[k][1], xa[k][2], xa[k][3], xa[k][0], xa[k][2]);
            mma_bf16(aG1, xa[k][0], xa[k][1], xa[k][2], xa[k][3], xa[k][1], xa[k][3]);
        }
        if (c == (g >> 1)) {
            sts64f(sb + OFF_STAT + hw * 128 + g * 8, aS[0], (g & 1) ? aG0[1] : aG0[0]);
            sts64f(sb + OFF_STAT + hw * 128 + (g + 8) * 8, aS[2], (g & 1) ? aG1[3] : aG1[2]);
        }
    }
    TS(1);
    bar_sync(BAR_STAT, 256);
    uint32_t m2[2];
    float rs[2];
    {
        const int t = g + 8 * (c & 1);
        float2 pv[8];
#pragma unroll
        for (int k = 0; k < 8; k++) pv[k] = lds64f(sb + OFF_STAT + k * 128 + t * 8);
        const float s = ((pv[0].x + pv[1].x) + (pv[2].x + pv[3].x)) + ((pv[4].x + pv[5].x) + (pv[6].x + pv[7].x));
        const float q = ((pv[0].y + pv[1].y) + (pv[2].y + pv[3].y)) + ((pv[4].y + pv[5].y) + (pv[6].y + pv[7].y));
        const float mean = s * (1.f / 512.f);
        const float var = fmaxf(fmaf(-mean, mean, q * (1.f / 512.f)), 0.f);
        const uint32_t mm = pack_bf16(mean, mean);
        const float sd = bf_round(sqrtaf(bf_round(bf_round(var) + 1e-5f)));
        const float rr = rcpaf(sd);
        if (tid < 32 && c < 2) sts32(sb + OFF_MS + 4 * t, (mm << 16) | (__float_as_uint(sd) >> 16));
        const uint32_t mo = __shfl_xor_sync(0xffffffffu, mm, 1);
        const float ro = __shfl_xor_sync(0xffffffffu, rr, 1);
        m2[0] = (c & 1) ? mo : mm; m2[1] = (c & 1) ? mm : mo;
        rs[0] = (c & 1) ? ro : rr; rs[1] = (c & 1) ? rr : ro;
    }
    {
        char* dst = (char*)P.xnT + (size_t)(tag & 1) * (128 * 16384) + (size_t)(16 * hw + (g >> 2)) * 16384 + cta * 128 + (g & 3) * 32 + 8 * c;
        if (tid < 8) { st_rlx16(P.hint + tid * 128 + cta, tag); sts32(sb + OFF_SEL + 8, tag); }
#pragma unroll
        for (int k = 0; k < 4; k++) {
#pragma unroll
            for (int r = 0; r < 4; r++) xa[k][r] = norm2(xa[k][r], m2[r & 1], rs[r & 1]);
            st_rlx64(dst + (size_t)k * (4 * 16384), ~movm(xa[k][0]), movm(xa[k][1]));
            st_rlx64(dst + (size_t)k * (4 * 16384) + 2 * 16384, ~movm(xa[k][2]), movm(xa[k][3]));
        }
    }
    TS(14);

    {
        float aR[4] = {0, 0, 0, 0};
#pragma unroll
        for (int k = 0; k < 4; k++) {
            const uint32_t wr = sb + OFF_WR + (32 * hw + 8 * k + c) * 4;
            mma_bf16(aR, xa[k][0], xa[k][1], xa[k][2], xa[k][3], lds32(wr), lds32(wr + 16));
            stsm_x4(sb + OFF_XNT + ta + 32 * k, xa[k][0], xa[k][1], xa[k][2], xa[k][3]);
        }
        if (c == 0) { stsf(sb + OFF_RP + g * 32 + hw * 4, aR[0]); stsf(sb + OFF_RP + (g + 8) * 32 + hw * 4, aR[2]); }
    }
    if (hw != 0) bar_arrive(BAR_R2, 256);
    else {
        bar_sync(BAR_R2, 256);
        const int t = lane & 15;
        const float4 v0 = lds128f(sb + OFF_RP + t * 32), v1 = lds128f(sb + OFF_RP + t * 32 + 16);
        const uint32_t rb = pack_bf16(((v0.x + v0.y) + (v0.z + v0.w)) + ((v1.x + v1.y) + (v1.z + v1.w)), 0.f);
        const uint32_t ord = (rb & 0x8000u) ? (~rb & 0xffffu) : (rb | 0x8000u);
        const uint32_t key = __reduce_max_sync(0xffffffffu, (ord << 16) | ((tag & 31u) << 11) | (uint32_t)(2047 - (16 * cta + t)));
        if (lane == 0) st_rlx64(rec, key, lds32(sb + OFF_MS + 4 * ((2047 - key) & 15)));
#pragma unroll 1
        for (int it = 0; it < kSpin; it++) {
            const uint4 h = ld_rlx128(P.hint + (cta & 7) * 128 + 4 * lane);
            if (__all_sync(0xffffffffu, (((h.x ^ tag) | (h.y ^ tag) | (h.z ^ tag) | (h.w ^ tag)) & 0xffffu) == 0)) break;
        }
    }
    TS(2);
    bar_sync(BAR_AUX, 256);
    TS(3);
    {
        const uint4* src = P.xnT + (size_t)(tag & 1) * (128 * 1024) + (size_t)cta * 1024 + tid;
        uint4 v[4];
#pragma unroll
        for (int r = 0; r < 4; r++) v[r] = ld_weak128(src + 256 * r);
#pragma unroll 1
        for (int it = 0; it < kSpin; it++) {
            bool ok = true;
#pragma unroll
            for (int r = 0; r < 4; r++) ok = ok && v[r].x != 0u && v[r].z != 0u;
            if (__all_sync(0xffffffffu, ok)) break;
#pragma unroll
            for (int r = 0; r < 4; r++) if (v[r].x == 0u || v[r].z == 0u) v[r] = ld_rlx128(src + 256 * r);
        }
        const uint32_t dst = sb + OFF_XNF + ((tid >> 1) & 3) * XNF_CH + 256 + (tid >> 3) * 32 + (tid & 1) * 16;
#pragma unroll
        for (int r = 0; r < 4; r++) sts128(dst + r * 1024, make_uint4(~v[r].x, v[r].y, ~v[r].z, v[r].w));
    }
    bar_arrive(BAR_XN, kThreads);
    TS(4);
    if (cta < kFFN && lane == 0) {
        const uint32_t mb = sb + OFF_MBAR;
        if (hw == 0) mbar_expect_tx(mb, 3 * 16384);
        if (hw < 4) tma_2d(sb + ((hw & 2) ? OFF_WU : OFF_WG) + (hw & 1) * 8192, (hw & 2) ? tmU : tmG, 16 * cta, (hw & 1) * 256, mb);
        tma_1d(sb + OFF_WD + (2 * hw) * ROW, P.w_down + (size_t)(16 * cta + 2 * hw) * kD, 1024, mb);
        tma_1d(sb + OFF_WD + (2 * hw + 1) * ROW, P.w_down + (size_t)(16 * cta + 2 * hw + 1) * kD, 1024, mb);
    }
    __syncwarp();
    uint32_t key, msw;
    if (hw == 1) {
        const uint32_t tag5 = (tag & 31u) << 11;
#pragma unroll 1
        for (int it = 0; it < kSpin; it++) {
            uint32_t bad = 0;
            key = 0; msw = 0;
#pragma unroll
            for (int i = 0; i < 4; i++) {
                const uint2 k2 = ld_rlx64(&P.rec[2 * (lane + 32 * i)]);
                bad |= (k2.x & 0xf800u) ^ tag5;
                if (k2.x > key) { key = k2.x; msw = k2.y; }
            }
            if (__all_sync(0xffffffffu, bad == 0)) break;
        }
        if (key == __reduce_max_sync(0xffffffffu, key)) sts64(sb + OFF_SEL, key, msw);
    }
    bar_sync(BAR_AUX, 256);
    { const uint2 km = lds64(sb + OFF_SEL); key = km.x; msw = km.y; }
    if (cta < kFFN) {
        const uint32_t xsel = ld_weak32((const uint32_t*)(P.u + (size_t)(2047 - (int)(key & 2047u)) * kD) + tid);
        sts32(sb + OFF_XS + 4 * tid, norm2(xsel, __byte_perm(msw, 0, 0x3232), rcpaf(__uint_as_float(msw << 16))));
    }
    const int idx = 2047 - (int)(key & 2047u);
    TS(6);
    if (hw == 0 && cta < kFFN) {
#pragma unroll 1
        for (int it = 0; it < kSpin && !mbar_try(sb + OFF_MBAR, 0); it++) { }
    }
    bar_sync(BAR_AUX, 256);
    if (hw >= 4) TS(13);
    if (cta < kFFN) {
        {
            float ag[4] = {0, 0, 0, 0}, au[4] = {0, 0, 0, 0};
            const uint32_t wa = sb + OFF_WG + (64 * hw + 8 * (lane >> 4) + (lane & 7)) * 32 + 16 * ((lane >> 3) & 1);
#pragma unroll 2
            for (int k = 0; k < 4; k++) {
                const uint32_t xs = sb + OFF_XS + (32 * hw + 8 * k + c) * 4;
                const uint32_t b0 = lds32(xs), b1 = lds32(xs + 16);
                uint32_t a0, a1, a2, a3;
                ldsm_x4_t(a0, a1, a2, a3, wa + 512 * k);
                mma_bf16(ag, a0, a1, a2, a3, b0, b1);
                ldsm_x4_t(a0, a1, a2, a3, wa + 16384 + 512 * k);
                mma_bf16(au, a0, a1, a2, a3, b0, b1);
            }
            if (c == 0) {
                const uint32_t fr = sb + OFF_FR + hw * 128 + 4 * g;
                stsf(fr, ag[0]); stsf(fr + 32, ag[2]); stsf(fr + 64, au[0]); stsf(fr + 96, au[2]);
            }
        }
        bar_sync(BAR_AUX, 256);
        {
            float gs = 0.f, us = 0.f;
#pragma unroll
            for (int k = 0; k < 4; k++) {
                const uint32_t fr = sb + OFF_FR + (4 * (lane >> 4) + k) * 128 + 4 * (lane & 15);
                gs += ldsf(fr); us += ldsf(fr + 64);
            }
            gs += __shfl_xor_sync(0xffffffffu, gs, 16); us += __shfl_xor_sync(0xffffffffu, us, 16);
            const float gb = bf_round(gs);
            const float hv = bf_round(bf_round(__fdividef(gb, 1.f + __expf(-gb))) * bf_round(us));
            const uint32_t b0 = pack_bf16(__shfl_sync(0xffffffffu, hv, 2 * c), __shfl_sync(0xffffffffu, hv, 2 * c + 1));
            const uint32_t b1 = pack_bf16(__shfl_sync(0xffffffffu, hv, 2 * c + 8), __shfl_sync(0xffffffffu, hv, 2 * c + 9));
            const uint32_t wa = sb + OFF_WD + (8 * (lane >> 4) + (lane & 7)) * ROW + (64 * hw + 8 * ((lane >> 3) & 1)) * 2;
            float y0 = 0.f, y1 = 0.f;
#pragma unroll
            for (int m = 0; m < 4; m++) {
                float d[4] = {0, 0, 0, 0};
                uint32_t a0, a1, a2, a3;
                ldsm_x4_t(a0, a1, a2, a3, wa + 32 * m);
                mma_bf16(d, a0, a1, a2, a3, b0, b1);
                if (c == m) { y0 = d[0]; y1 = d[2]; }
            }
            uint32_t* dst = P.part + (size_t)(tag & 1) * (kFFN * 512) + cta * 512 + 64 * hw + 16 * c + g;
            st_rlx32(dst, ~__float_as_uint(y0));
            st_rlx32(dst + 8, ~__float_as_uint(y1));
        }
        bar_sync(BAR_AUX, 256);
        if (tid < 8) st_rlx8((uint8_t*)(P.hint + tid * 128 + cta) + 2, tag);
    }
    TS(8);
    {
        const uint4 z = make_uint4(0, 0, 0, 0);
        uint4* zx = P.xnT + (size_t)((tag & 1) ^ 1) * (128 * 1024) + (size_t)cta * 1024 + tid;
#pragma unroll
        for (int r = 0; r < 4; r++) zx[256 * r] = z;
        if (cta < kFFN && tid < 128) ((uint4*)P.part)[((tag & 1) ^ 1) * (kFFN * 128) + cta * 128 + tid] = z;
    }
    if (hw == 0) {
#pragma unroll 1
        for (int it = 0; it < kSpin; it++) {
            const uint4 h = ld_rlx128(P.hint + (cta & 7) * 128 + 4 * min(lane, kFFN / 4 - 1));
            const uint32_t t8 = tag << 16;
            if (__all_sync(0xffffffffu, (((h.x ^ t8) | (h.y ^ t8) | (h.z ^ t8) | (h.w ^ t8)) & 0xff0000u) == 0)) break;
        }
    }
    bar_sync(BAR_AUX, 256);
    {
        if (hw < 4) {
            const uint32_t* src = P.part + (size_t)(tag & 1) * (kFFN * 512) + min(tid, kFFN - 1) * 512 + 4 * cta;
            uint4 p;
#pragma unroll 1
            for (int it = 0; it < kSpin; it++) {
                p = ld_rlx128(src);
                if (__all_sync(0xffffffffu, p.x != 0u && p.y != 0u && p.z != 0u && p.w != 0u)) break;
            }
            const bool on = tid < kFFN;
            float y0 = on ? __uint_as_float(~p.x) : 0.f, y1 = on ? __uint_as_float(~p.y) : 0.f;
            float y2 = on ? __uint_as_float(~p.z) : 0.f, y3 = on ? __uint_as_float(~p.w) : 0.f;
            TS(13);
#pragma unroll
            for (int o = 1; o <= 16; o <<= 1) {
                y0 += __shfl_xor_sync(0xffffffffu, y0, o); y1 += __shfl_xor_sync(0xffffffffu, y1, o);
                y2 += __shfl_xor_sync(0xffffffffu, y2, o); y3 += __shfl_xor_sync(0xffffffffu, y3, o);
            }
            if (lane == 0) sts128f(sb + OFF_YR + hw * 16, y0, y1, y2, y3);
        }
        TS(7);
        bar_sync(BAR_AUX, 256);
        if (tid < 4) {
            float y = 0.f;
#pragma unroll
            for (int k = 0; k < 4; k++) y += ldsf(sb + OFF_YR + k * 16 + 4 * tid);
            const uint32_t ord = key >> 16;
            const float r = __uint_as_float(((ord & 0x8000u) ? (ord & 0x7fffu) : (~ord & 0xffffu)) << 16);
            const float rsel = bf_round(__fdividef(1.f, 1.f + __expf(-r)));
            st_rlx32(rec + 4 + tid, (tag << 16) | (pack_bf16(bf_round(y) * rsel, 0.f) & 0xffffu));
        }
    }
    TS(9);
    {
        const int tsel = ((idx >> 4) == cta) ? (idx & 15) : -1;
        TS(10);
        bar_sync(BAR_Y, kThreads);
        TS(11);
#pragma unroll 2
        for (int k = 0; k < 4; k++) {
            uint32_t x[4], n[4];
            ldsm_x4(x[0], x[1], x[2], x[3], sb + OFF_XT + ta + 32 * k);
            ldsm_x4(n[0], n[1], n[2], n[3], sb + OFF_XNT + ta + 32 * k);
#pragma unroll
            for (int hc = 0; hc < 2; hc++) {
                const int cp = 32 * hw + 8 * k + 4 * hc + c;
                const uint32_t y0 = ~lds32(sb + OFF_YT + cp * 64 + g * 4), y1 = ~lds32(sb + OFF_YT + cp * 64 + 32 + g * 4);
                const uint32_t ds = lds32(sb + OFF_DS + 4 * cp);
#pragma unroll
                for (int ht = 0; ht < 2; ht++) {
                    const int r = ht + 2 * hc;
                    const uint32_t yb = __byte_perm(y0, y1, ht ? 0x7632 : 0x5410);
                    x[r] = badd2(badd2(x[r], badd2(yb, bmul2(n[r], ds))), n[r]);
                }
            }
            stsm_x4(sb + OFF_OUT + ta + 32 * k, x[0], x[1], x[2], x[3]);
        }
        __syncwarp();
#pragma unroll
        for (int r = 0; r < 4; r++) {
            const int row = 4 * r + (lane >> 3);
            const uint4 v = lds128(sb + OFF_OUT + row * ROW + hw * 128 + (lane & 7) * 16);
            if (row != tsel) *(uint4*)(P.out + (size_t)(16 * cta + row) * kD + 64 * hw + (lane & 7) * 8) = v;
        }
        if (tsel >= 0) {
            const uint32_t* us = (const uint32_t*)&P.rec[2 * (tid >> 1) + 1] + 2 * (tid & 1);
            const uint32_t xw = lds32(sb + OFF_XT + tsel * ROW + 4 * tid), nw = lds32(sb + OFF_XNT + tsel * ROW + 4 * tid);
            const uint32_t yo = sb + OFF_YT + tid * 64 + (tsel & 7) * 4;
            const uint32_t yb = __byte_perm(~lds32(yo), ~lds32(yo + 32), (tsel & 8) ? 0x7632 : 0x5410);
            const uint32_t s1 = badd2(xw, badd2(yb, bmul2(nw, lds32(sb + OFF_DS + 4 * tid))));
            uint32_t a, b;
#pragma unroll 1
            for (int it = 0; it < kSpin; it++) {
                a = ld_rlx32(us); b = ld_rlx32(us + 1);
                if (__all_sync(0xffffffffu, (a >> 16) == tag && (b >> 16) == tag)) break;
            }
            ((uint32_t*)(P.out + (size_t)idx * kD))[tid] = badd2(s1, badd2(nw, __byte_perm(a, b, 0x5410)));
        }
    }
    TS(12); TDUMP();
}

__global__ void __launch_bounds__(kThreads, 1) fused_kernel(const Params P, const __grid_constant__ CUtensorMap tmG,
                                                             const __grid_constant__ CUtensorMap tmU) {
    extern __shared__ __align__(128) unsigned char smem[];
    const uint32_t sb = (uint32_t)__cvta_generic_to_shared(smem);
    const int warp = threadIdx.x >> 5, lane = threadIdx.x & 31;
    const int cta = blockIdx.x;
    const int w = warp & 3, half = (warp >> 2) & 1;
    TS(0);
    ModeRegs q;
    uint32_t prev_rec = 0;
    if (warp >= 8) {
        {
        const size_t po = (size_t)(4 * cta + w) * 128 + 64 * half + 2 * lane;
        q.ar = ld_nc32(P.A_re + po); q.ai = ld_nc32(P.A_im + po); q.br = ld_nc32(P.B_re + po);
        q.bi = ld_nc32(P.B_im + po); q.cr = ld_nc32(P.C_re + po); q.ci = ld_nc32(P.C_im + po);
        q.ldt = ld_nc16(P.log_dt + 4 * cta + w);
        }
        bar_arrive(BAR_GO, kThreads);
    } else {
        const int tid = threadIdx.x;
        bar_sync(BAR_GO, kThreads);
        const uint32_t xd = sb + OFF_XT + (tid >> 6) * ROW + (tid & 63) * 16;
        const __nv_bfloat16* xs = P.u + (size_t)cta * 16 * kD + tid * 8;
#pragma unroll
        for (int i = 0; i < 4; i++) cp_async16(xd + 4 * ROW * i, xs + 2048 * i);
        if (tid < 128) cp_async16(sb + OFF_WR + tid * 16, (tid < 64 ? P.w_r : P.Dskip - 512) + tid * 8);
        asm volatile("cp.async.commit_group;" ::: "memory");
        prev_rec = ld_rlx32(P.hint + (cta & 7) * 128 + cta);
        aux_warp(P, &tmG, &tmU, sb, cta, warp, lane, prev_rec);
        return;
    }
    if (half) {
        const uint32_t pt = sb + OFF_PT + w * (PT_CH_W * 4);
        const uint4 z = make_uint4(0, 0, 0, 0);
#pragma unroll 1
        for (int i = lane; i < (PT_CH_W - PT_L) / 4; i += 32) sts128(pt + 4 * PT_L + 16 * i, z);
        if (lane < 16) sts128(sb + OFF_XNF + w * XNF_CH + lane * 16, z);
    }
    kgen_tables(P, q, sb, w, half, lane);
    if (!half) conv_warp(P, sb, cta, w, lane);
    else help_warp(P, sb, cta, w, lane);
    y_exchange(P, sb, cta, threadIdx.x - 256);
}

}

extern "C" void kernel_launch(void* const* d_in, const int* in_sizes, int n_in, void* d_out, int out_size) {
    using namespace s4moe;
    (void)in_sizes; (void)n_in; (void)out_size;
    Params P;
    P.u = (const __nv_bfloat16*)d_in[0];
    P.A_re = (const __nv_bfloat16*)d_in[1];
    P.A_im = (const __nv_bfloat16*)d_in[2];
    P.B_re = (const __nv_bfloat16*)d_in[3];
    P.B_im = (const __nv_bfloat16*)d_in[4];
    P.C_re = (const __nv_bfloat16*)d_in[5];
    P.C_im = (const __nv_bfloat16*)d_in[6];
    P.log_dt = (const __nv_bfloat16*)d_in[7];
    P.Dskip = (const __nv_bfloat16*)d_in[8];
    P.w_r = (const __nv_bfloat16*)d_in[10];
    P.w_gate = (const __nv_bfloat16*)d_in[11];
    P.w_up = (const __nv_bfloat16*)d_in[12];
    P.w_down = (const __nv_bfloat16*)d_in[13];
    P.out = (__nv_bfloat16*)d_out;
    typedef CUresult (*EncodeFn)(CUtensorMap*, CUtensorMapDataType, cuuint32_t, void*, const cuuint64_t*, const cuuint64_t*,
                                 const cuuint32_t*, const cuuint32_t*, CUtensorMapInterleave, CUtensorMapSwizzle,
                                 CUtensorMapL2promotion, CUtensorMapFloatOOBfill);
    static EncodeFn encode = nullptr;
    static bool init = false;
    static void *p_rec, *p_hint, *p_xnT, *p_yT, *p_part, *p_dbg = nullptr, *p_dbgK = nullptr;
    if (!init) {
        init = true;
        cudaGetSymbolAddress(&p_rec, g_rec);
        cudaGetSymbolAddress(&p_hint, g_hint);
        cudaGetSymbolAddress(&p_xnT, g_xnT);
        cudaGetSymbolAddress(&p_yT, g_yT);
        cudaGetSymbolAddress(&p_part, g_part);
        void* fn = nullptr;
        cudaDriverEntryPointQueryResult qr;
        cudaGetDriverEntryPoint("cuTensorMapEncodeTiled", &fn, cudaEnableDefault, &qr);
        encode = (EncodeFn)fn;
        cudaFuncSetAttribute(fused_kernel, cudaFuncAttributeMaxDynamicSharedMemorySize, SMEM_BYTES);
    }
    CUtensorMap tmG, tmU;
    const cuuint64_t dims[2] = {(cuuint64_t)kF, (cuuint64_t)kD}, strides[1] = {(cuuint64_t)kF * 2};
    const cuuint32_t box[2] = {16, 256}, estr[2] = {1, 1};
    encode(&tmG, CU_TENSOR_MAP_DATA_TYPE_BFLOAT16, 2, d_in[11], dims, strides, box, estr, CU_TENSOR_MAP_INTERLEAVE_NONE,
           CU_TENSOR_MAP_SWIZZLE_NONE, CU_TENSOR_MAP_L2_PROMOTION_L2_128B, CU_TENSOR_MAP_FLOAT_OOB_FILL_NONE);
    encode(&tmU, CU_TENSOR_MAP_DATA_TYPE_BFLOAT16, 2, d_in[12], dims, strides, box, estr, CU_TENSOR_MAP_INTERLEAVE_NONE,
           CU_TENSOR_MAP_SWIZZLE_NONE, CU_TENSOR_MAP_L2_PROMOTION_L2_128B, CU_TENSOR_MAP_FLOAT_OOB_FILL_NONE);
    P.rec = (uint4*)p_rec; P.hint = (uint32_t*)p_hint; P.xnT = (uint4*)p_xnT; P.yT = (uint32_t*)p_yT; P.part = (uint32_t*)p_part;
    P.dbg = (long long*)p_dbg; P.dbgK = (float*)p_dbgK;
    fused_kernel<<<kCTA, kThreads, SMEM_BYTES>>>(P, tmG, tmU);
}
```
